```python
import torch

def _softmax(x, axis=-1):
    return torch.softmax(x, dim=axis)
def _gelu(x):
    return torch.nn.functional.gelu(x, approximate="tanh")
def _silu(x):
    return torch.nn.functional.silu(x)
def _sigmoid(x):
    return torch.sigmoid(x)
def _layernorm(x, axis=-1, eps=1e-5):
    m = x.mean(dim=axis, keepdim=True)
    v = x.var(dim=axis, keepdim=True, unbiased=False)
    return (x - m) / torch.sqrt(v + eps)
def _scatter_add(tgt, idx, src, axis=0):
    return tgt.clone().index_add_(axis, idx, src)
def _segment_sum(src, seg, n):
    out = torch.zeros((n,) + src.shape[1:], dtype=src.dtype)
    return out.index_add_(0, seg, src)
def _pad(x, pw):
    flat = tuple(v for pair in reversed(pw) for v in pair)
    return torch.nn.functional.pad(x, flat)

kernel_name = 'recurrent_scan__spectral_fnet__geglu_ffn__prompt'

def setup_inputs():

    _w = (lambda a: (lambda t: t.to(torch.bfloat16) if t.is_floating_point() else t)(torch.as_tensor(a)))
    def _A_setup():
        B, S, D = 1, 2048, 448
        ns = torch.arange(S)[:, None] * torch.arange(S)[None, :]
        nd = torch.arange(D)[:, None] * torch.arange(D)[None, :]
        Ws_re = torch.cos(-2.0 * torch.pi * ns / S).to(float)
        Ws_im = torch.sin(-2.0 * torch.pi * ns / S).to(float)
        Wd_re = torch.cos(-2.0 * torch.pi * nd / D).to(float)
        Wd_im = torch.sin(-2.0 * torch.pi * nd / D).to(float)
        return {
            "x": _w((lambda *s: torch.randn(*s, dtype=torch.bfloat16) * 0.05)(B, S, D)),
            "dft_seq_re": _w(Ws_re),
            "dft_seq_im": _w(Ws_im),
            "dft_hid_re": _w(Wd_re),
            "dft_hid_im": _w(Wd_im),
        }
    _A_in = _A_setup()

    def _B_setup():
        B, S, D, F = 1, 2048, 448, 1792
        return {
            "x": _w((lambda *s: torch.randn(*s, dtype=torch.bfloat16) * 0.05)(B, S, D)),
            "w_gate": _w((lambda *s: torch.randn(*s, dtype=torch.bfloat16) * 0.05)(D, F)),
            "w_up": _w((lambda *s: torch.randn(*s, dtype=torch.bfloat16) * 0.05)(D, F)),
            "w_down": _w((lambda *s: torch.randn(*s, dtype=torch.bfloat16) * 0.05)(F, D)),
        }
    _B_in = _B_setup()

    return {
        "A_x": _A_in["x"],
        "A_dft_seq_re": _A_in["dft_seq_re"],
        "A_dft_seq_im": _A_in["dft_seq_im"],
        "A_dft_hid_re": _A_in["dft_hid_re"],
        "A_dft_hid_im": _A_in["dft_hid_im"],
        "B_x": _B_in["x"],
        "B_w_gate": _B_in["w_gate"],
        "B_w_up": _B_in["w_up"],
        "B_w_down": _B_in["w_down"],
    }

def reference(A_x, A_dft_seq_re, A_dft_seq_im, A_dft_hid_re, A_dft_hid_im, B_x, B_w_gate, B_w_up, B_w_down):
    def _A_ref(x, dft_seq_re, dft_seq_im, dft_hid_re, dft_hid_im):
        a = torch.einsum("bsd,ed->bse", x, dft_hid_re)
        b = torch.einsum("bsd,ed->bse", x, dft_hid_im)
        y = torch.einsum("ts,bse->bte", dft_seq_re, a) - torch.einsum("ts,bse->bte", dft_seq_im, b)
        return y

    def _B_ref(x, w_gate, w_up, w_down):
        return (_gelu(x @ w_gate) * (x @ w_up)) @ w_down

    x = A_x
    xn = _layernorm(x, axis=-1)
    s = _A_ref(xn, A_dft_seq_re, A_dft_seq_im, A_dft_hid_re, A_dft_hid_im)
    g = _silu(_B_ref(xn, B_w_gate, B_w_up, B_w_down))
    return x + s * g
```

```cpp
#include <cuda_runtime.h>
#include <cuda_bf16.h>
#include <cuda.h>
#include <stdint.h>

namespace {

constexpr int S_ = 2048, D_ = 448, F_ = 1792;

__device__ __align__(1024) __nv_bfloat16 g_abT[896 * 2048];
__device__ __align__(1024) __nv_bfloat16 g_h[2048 * 1792];
__device__ __align__(1024) float4 g_part[32 * 5 * 4 * 7 * 256];
__device__ unsigned int g_cnt[32];

__device__ __forceinline__ uint32_t s2u(const void* p) { return (uint32_t)__cvta_generic_to_shared(p); }
__device__ __forceinline__ void mbar_init(uint32_t b, int c) {
    asm volatile("mbarrier.init.shared::cta.b64 [%0], %1;" ::"r"(b), "r"(c));
}
__device__ __forceinline__ void mbar_expect(uint32_t b, uint32_t bytes) {
    asm volatile("mbarrier.arrive.expect_tx.shared::cta.b64 _, [%0], %1;" ::"r"(b), "r"(bytes) : "memory");
}
__device__ __forceinline__ void mbar_wait(uint32_t b, uint32_t ph) {
    uint32_t ok;
    do {
        asm volatile("{\n.reg .pred p;\nmbarrier.try_wait.parity.shared::cta.b64 p, [%1], %2;\nselp.u32 %0, 1, 0, p;\n}"
                     : "=r"(ok) : "r"(b), "r"(ph) : "memory");
    } while (!ok);
}
__device__ __forceinline__ void mbar_wait_cl(uint32_t b, uint32_t ph) {
    uint32_t ok;
    do {
        asm volatile("{\n.reg .pred p;\nmbarrier.try_wait.parity.acquire.cluster.shared::cta.b64 p, [%1], %2;\nselp.u32 %0, 1, 0, p;\n}"
                     : "=r"(ok) : "r"(b), "r"(ph) : "memory");
    } while (!ok);
}
__device__ __forceinline__ void mbar_arrive_both(uint32_t b) {
    asm volatile("{\n.reg .b32 r0, r1;\n"
                 "mapa.shared::cluster.u32 r0, %0, 0;\n"
                 "mapa.shared::cluster.u32 r1, %0, 1;\n"
                 "mbarrier.arrive.release.cluster.shared::cluster.b64 _, [r0];\n"
                 "mbarrier.arrive.release.cluster.shared::cluster.b64 _, [r1];\n}"
                 ::"r"(b) : "memory");
}
__device__ __forceinline__ void tma_load(uint32_t dst, const CUtensorMap* m, uint32_t bar, int c0, int c1) {
    asm volatile("cp.async.bulk.tensor.2d.shared::cluster.global.mbarrier::complete_tx::bytes [%0], [%1, {%3, %4}], [%2];"
                 ::"r"(dst), "l"(m), "r"(bar), "r"(c0), "r"(c1) : "memory");
}
__device__ __forceinline__ void tma_load_mc(uint32_t dst, const CUtensorMap* m, uint32_t bar, int c0, int c1) {
    asm volatile("cp.async.bulk.tensor.2d.shared::cluster.global.mbarrier::complete_tx::bytes.multicast::cluster [%0], [%1, {%3, %4}], [%2], %5;"
                 ::"r"(dst), "l"(m), "r"(bar), "r"(c0), "r"(c1), "h"((uint16_t)3) : "memory");
}
__device__ __forceinline__ void tma_store(const CUtensorMap* m, uint32_t src, int c0, int c1) {
    asm volatile("cp.async.bulk.tensor.2d.global.shared::cta.bulk_group [%0, {%2, %3}], [%1];"
                 ::"l"(m), "r"(src), "r"(c0), "r"(c1) : "memory");
}
__device__ __forceinline__ void bulk_commit() { asm volatile("cp.async.bulk.commit_group;" ::: "memory"); }
__device__ __forceinline__ void bulk_wait_read0() { asm volatile("cp.async.bulk.wait_group.read 0;" ::: "memory"); }
__device__ __forceinline__ void bulk_wait0() { asm volatile("cp.async.bulk.wait_group 0;" ::: "memory"); }
__device__ __forceinline__ void fence_async() { asm volatile("fence.proxy.async.shared::cta;" ::: "memory"); }
__device__ __forceinline__ void cluster_sync() {
    asm volatile("barrier.cluster.arrive.release.aligned;\nbarrier.cluster.wait.acquire.aligned;" ::: "memory");
}
__device__ __forceinline__ void bar_sync(int id, int n) { asm volatile("bar.sync %0, %1;" ::"r"(id), "r"(n) : "memory"); }
__device__ __forceinline__ void wg_arrive() { asm volatile("wgmma.fence.sync.aligned;" ::: "memory"); }
__device__ __forceinline__ void wg_commit() { asm volatile("wgmma.commit_group.sync.aligned;" ::: "memory"); }
template <int N> __device__ __forceinline__ void wg_wait() { asm volatile("wgmma.wait_group.sync.aligned %0;" ::"n"(N) : "memory"); }
__device__ __forceinline__ void prefetch_tmap(const CUtensorMap* m) {
    asm volatile("prefetch.tensormap [%0];" ::"l"(m) : "memory");
}
__device__ __forceinline__ void stmat4(uint32_t a, uint32_t r0, uint32_t r1, uint32_t r2, uint32_t r3) {
    asm volatile("stmatrix.sync.aligned.m8n8.x4.shared.b16 [%0], {%1, %2, %3, %4};" ::"r"(a), "r"(r0), "r"(r1), "r"(r2), "r"(r3) : "memory");
}
__device__ __forceinline__ void stmat4t(uint32_t a, uint32_t r0, uint32_t r1, uint32_t r2, uint32_t r3) {
    asm volatile("stmatrix.sync.aligned.m8n8.x4.trans.shared.b16 [%0], {%1, %2, %3, %4};" ::"r"(a), "r"(r0), "r"(r1), "r"(r2), "r"(r3) : "memory");
}
__device__ __forceinline__ uint64_t mkdesc(uint32_t addr, uint32_t lbo, uint32_t sbo) {
    return (uint64_t)((addr & 0x3FFFF) >> 4) | ((uint64_t)(lbo >> 4) << 16) | ((uint64_t)(sbo >> 4) << 32) | (1ull << 62);
}
__device__ __forceinline__ uint32_t pack_bf16(float lo, float hi) {
    uint32_t r;
    asm("cvt.rn.bf16x2.f32 %0, %1, %2;" : "=r"(r) : "f"(hi), "f"(lo));
    return r;
}
__device__ __forceinline__ float bf_lo(uint32_t u) { return __uint_as_float(u << 16); }
__device__ __forceinline__ float bf_hi(uint32_t u) { return __uint_as_float(u & 0xffff0000u); }
__device__ __forceinline__ float rbf(float v) { return __bfloat162float(__float2bfloat16_rn(v)); }
__device__ __forceinline__ float tanh_fast(float x) { float r; asm("tanh.approx.f32 %0, %1;" : "=f"(r) : "f"(x)); return r; }
__device__ __forceinline__ float gelu_tanh(float x) {
    float u = x * fmaf(x * x, 0.0356774081f, 0.7978845608f);
    float hx = 0.5f * x;
    return fmaf(hx, tanh_fast(u), hx);
}

template <int TB>
__device__ __forceinline__ void wgmma_n64(float (&d)[64], uint64_t da, uint64_t db, int scaleD) {
    asm volatile("{\n.reg .pred p;\nsetp.ne.b32 p, %34, 0;\n"
        "wgmma.mma_async.sync.aligned.m64n64k16.f32.bf16.bf16 {%0, %1, %2, %3, %4, %5, %6, %7, %8, %9, %10, %11, %12, %13, %14, %15, %16, %17, %18, %19, %20, %21, %22, %23, %24, %25, %26, %27, %28, %29, %30, %31}, %32, %33, p, 1, 1, 0, %35;\n}\n"
        : "+f"(d[0]), "+f"(d[1]), "+f"(d[2]), "+f"(d[3]), "+f"(d[4]), "+f"(d[5]), "+f"(d[6]), "+f"(d[7]), "+f"(d[8]), "+f"(d[9]), "+f"(d[10]), "+f"(d[11]), "+f"(d[12]), "+f"(d[13]), "+f"(d[14]), "+f"(d[15]), "+f"(d[16]), "+f"(d[17]), "+f"(d[18]), "+f"(d[19]), "+f"(d[20]), "+f"(d[21]), "+f"(d[22]), "+f"(d[23]), "+f"(d[24]), "+f"(d[25]), "+f"(d[26]), "+f"(d[27]), "+f"(d[28]), "+f"(d[29]), "+f"(d[30]), "+f"(d[31])
        : "l"(da), "l"(db), "r"(scaleD), "n"(TB));
}
template <int TB>
__device__ __forceinline__ void wgmma_n128(float (&d)[64], uint64_t da, uint64_t db, int scaleD) {
    asm volatile("{\n.reg .pred p;\nsetp.ne.b32 p, %66, 0;\n"
        "wgmma.mma_async.sync.aligned.m64n128k16.f32.bf16.bf16 {%0, %1, %2, %3, %4, %5, %6, %7, %8, %9, %10, %11, %12, %13, %14, %15, %16, %17, %18, %19, %20, %21, %22, %23, %24, %25, %26, %27, %28, %29, %30, %31, %32, %33, %34, %35, %36, %37, %38, %39, %40, %41, %42, %43, %44, %45, %46, %47, %48, %49, %50, %51, %52, %53, %54, %55, %56, %57, %58, %59, %60, %61, %62, %63}, %64, %65, p, 1, 1, 0, %67;\n}\n"
        : "+f"(d[0]), "+f"(d[1]), "+f"(d[2]), "+f"(d[3]), "+f"(d[4]), "+f"(d[5]), "+f"(d[6]), "+f"(d[7]), "+f"(d[8]), "+f"(d[9]), "+f"(d[10]), "+f"(d[11]), "+f"(d[12]), "+f"(d[13]), "+f"(d[14]), "+f"(d[15]), "+f"(d[16]), "+f"(d[17]), "+f"(d[18]), "+f"(d[19]), "+f"(d[20]), "+f"(d[21]), "+f"(d[22]), "+f"(d[23]), "+f"(d[24]), "+f"(d[25]), "+f"(d[26]), "+f"(d[27]), "+f"(d[28]), "+f"(d[29]), "+f"(d[30]), "+f"(d[31]), "+f"(d[32]), "+f"(d[33]), "+f"(d[34]), "+f"(d[35]), "+f"(d[36]), "+f"(d[37]), "+f"(d[38]), "+f"(d[39]), "+f"(d[40]), "+f"(d[41]), "+f"(d[42]), "+f"(d[43]), "+f"(d[44]), "+f"(d[45]), "+f"(d[46]), "+f"(d[47]), "+f"(d[48]), "+f"(d[49]), "+f"(d[50]), "+f"(d[51]), "+f"(d[52]), "+f"(d[53]), "+f"(d[54]), "+f"(d[55]), "+f"(d[56]), "+f"(d[57]), "+f"(d[58]), "+f"(d[59]), "+f"(d[60]), "+f"(d[61]), "+f"(d[62]), "+f"(d[63])
        : "l"(da), "l"(db), "r"(scaleD), "n"(TB));
}
template <int TB>
__device__ __forceinline__ void wgmma_n224(float (&d)[112], uint64_t da, uint64_t db, int scaleD) {
    asm volatile("{\n.reg .pred p;\nsetp.ne.b32 p, %114, 0;\n"
        "wgmma.mma_async.sync.aligned.m64n224k16.f32.bf16.bf16 {%0, %1, %2, %3, %4, %5, %6, %7, %8, %9, %10, %11, %12, %13, %14, %15, %16, %17, %18, %19, %20, %21, %22, %23, %24, %25, %26, %27, %28, %29, %30, %31, %32, %33, %34, %35, %36, %37, %38, %39, %40, %41, %42, %43, %44, %45, %46, %47, %48, %49, %50, %51, %52, %53, %54, %55, %56, %57, %58, %59, %60, %61, %62, %63, %64, %65, %66, %67, %68, %69, %70, %71, %72, %73, %74, %75, %76, %77, %78, %79, %80, %81, %82, %83, %84, %85, %86, %87, %88, %89, %90, %91, %92, %93, %94, %95, %96, %97, %98, %99, %100, %101, %102, %103, %104, %105, %106, %107, %108, %109, %110, %111}, %112, %113, p, 1, 1, 0, %115;\n}\n"
        : "+f"(d[0]), "+f"(d[1]), "+f"(d[2]), "+f"(d[3]), "+f"(d[4]), "+f"(d[5]), "+f"(d[6]), "+f"(d[7]), "+f"(d[8]), "+f"(d[9]), "+f"(d[10]), "+f"(d[11]), "+f"(d[12]), "+f"(d[13]), "+f"(d[14]), "+f"(d[15]), "+f"(d[16]), "+f"(d[17]), "+f"(d[18]), "+f"(d[19]), "+f"(d[20]), "+f"(d[21]), "+f"(d[22]), "+f"(d[23]), "+f"(d[24]), "+f"(d[25]), "+f"(d[26]), "+f"(d[27]), "+f"(d[28]), "+f"(d[29]), "+f"(d[30]), "+f"(d[31]), "+f"(d[32]), "+f"(d[33]), "+f"(d[34]), "+f"(d[35]), "+f"(d[36]), "+f"(d[37]), "+f"(d[38]), "+f"(d[39]), "+f"(d[40]), "+f"(d[41]), "+f"(d[42]), "+f"(d[43]), "+f"(d[44]), "+f"(d[45]), "+f"(d[46]), "+f"(d[47]), "+f"(d[48]), "+f"(d[49]), "+f"(d[50]), "+f"(d[51]), "+f"(d[52]), "+f"(d[53]), "+f"(d[54]), "+f"(d[55]), "+f"(d[56]), "+f"(d[57]), "+f"(d[58]), "+f"(d[59]), "+f"(d[60]), "+f"(d[61]), "+f"(d[62]), "+f"(d[63]), "+f"(d[64]), "+f"(d[65]), "+f"(d[66]), "+f"(d[67]), "+f"(d[68]), "+f"(d[69]), "+f"(d[70]), "+f"(d[71]), "+f"(d[72]), "+f"(d[73]), "+f"(d[74]), "+f"(d[75]), "+f"(d[76]), "+f"(d[77]), "+f"(d[78]), "+f"(d[79]), "+f"(d[80]), "+f"(d[81]), "+f"(d[82]), "+f"(d[83]), "+f"(d[84]), "+f"(d[85]), "+f"(d[86]), "+f"(d[87]), "+f"(d[88]), "+f"(d[89]), "+f"(d[90]), "+f"(d[91]), "+f"(d[92]), "+f"(d[93]), "+f"(d[94]), "+f"(d[95]), "+f"(d[96]), "+f"(d[97]), "+f"(d[98]), "+f"(d[99]), "+f"(d[100]), "+f"(d[101]), "+f"(d[102]), "+f"(d[103]), "+f"(d[104]), "+f"(d[105]), "+f"(d[106]), "+f"(d[107]), "+f"(d[108]), "+f"(d[109]), "+f"(d[110]), "+f"(d[111])
        : "l"(da), "l"(db), "r"(scaleD), "n"(TB));
}


constexpr int KA_STAGES = 5;
constexpr int KA_XN = 0;
constexpr int KA_B = 7 * 16384;
constexpr int KA_STG = KA_B + KA_STAGES * 16384;
constexpr int KA_BAR = KA_STG + 2 * 16384;
constexpr int KA_SMEM = KA_BAR + 128 + 1024;

enum { P_H = 0, P_AB128 = 1, P_AB64 = 2 };
__device__ __forceinline__ void ka_pass(int j, int p, int& type, int& atom) {
    if (j < 7) {
        if (p < 4) { type = P_H; atom = 4 * j + p; } else { type = P_AB64; atom = j; }
    } else {
        if (p < 3) { type = P_AB128; atom = 7 + 2 * p; } else { type = P_AB64; atom = 13; }
    }
}

__global__ void __launch_bounds__(288, 1)
kernel_a(const __nv_bfloat16* __restrict__ x,
         const __grid_constant__ CUtensorMap tm_wg, const __grid_constant__ CUtensorMap tm_wu,
         const __grid_constant__ CUtensorMap tm_hre, const __grid_constant__ CUtensorMap tm_him,
         const __grid_constant__ CUtensorMap tm_h, const __grid_constant__ CUtensorMap tm_abT_st,
         const __nv_bfloat16* __restrict__ seq_re, const __nv_bfloat16* __restrict__ seq_im) {
    extern __shared__ unsigned char smem_raw[];
    const uint32_t sb = (s2u(smem_raw) + 1023) & ~1023u;
    const int tid = threadIdx.x, warp = tid >> 5, lane = tid & 31;
    const int rank = blockIdx.x & 1;
    const int cid = blockIdx.x >> 1;
    const int j = cid & 7;
    const int rb = (cid >> 3) * 2 + rank;
    const int npass = (j < 7) ? 5 : 4;
    const uint32_t bar_full = sb + KA_BAR, bar_empty = sb + KA_BAR + 64;

    if (tid == 0) {
        for (int i = 0; i < KA_STAGES; i++) { mbar_init(bar_full + 8 * i, 1); mbar_init(bar_empty + 8 * i, 8); }
        asm volatile("fence.mbarrier_init.release.cluster;" ::: "memory");
    }
    if (blockIdx.x == 0 && tid < 32) g_cnt[tid] = 0;
    asm volatile("griddepcontrol.launch_dependents;" ::: "memory");
    cluster_sync();

    if (warp == 8) {
        if (lane == 0) {
            int idx = 0;
            for (int p = 0; p < npass; p++) {
                int type, atom;
                ka_pass(j, p, type, atom);
                for (int kb = 0; kb < 7; kb++, idx++) {
                    const int st = idx % KA_STAGES;
                    const uint32_t ph = (idx / KA_STAGES) & 1;
                    mbar_wait_cl(bar_empty + 8 * st, ph ^ 1);
                    const uint32_t dst = sb + KA_B + st * 16384;
                    const uint32_t fb = bar_full + 8 * st;
                    mbar_expect(fb, type == P_AB64 ? 8192 : 16384);
                    if (type == P_H) {
                        tma_load_mc(dst + rank * 8192, rank ? &tm_wu : &tm_wg, fb, atom * 64, kb * 64);
                    } else if (type == P_AB128) {
                        const int a = atom + rank;
                        tma_load_mc(dst + rank * 8192, a < 7 ? &tm_hre : &tm_him, fb, kb * 64, (a < 7 ? a : a - 7) * 64);
                    } else if (rank == 0) {
                        tma_load_mc(dst, atom < 7 ? &tm_hre : &tm_him, fb, kb * 64, (atom < 7 ? atom : atom - 7) * 64);
                    }
                    if (idx == KA_STAGES - 1) {
                        const char* base = (const char*)((blockIdx.x < 64) ? seq_re : seq_im) + (size_t)(blockIdx.x & 63) * 131072;
                        for (int q = 0; q < 8; q++)
                            asm volatile("cp.async.bulk.prefetch.L2.global [%0], %1;" ::"l"(base + q * 16384), "r"(16384) : "memory");
                    }
                }
            }
        }
    } else {
        {
            const int l8 = lane & 7, sub = lane >> 3;
#pragma unroll 2
            for (int it = 0; it < 4; it++) {
                const int row = warp * 16 + it * 4 + sub;
                const uint4* src = reinterpret_cast<const uint4*>(x + (size_t)(rb * 128 + row) * D_) + l8;
                uint4 v[7];
#pragma unroll
                for (int i = 0; i < 7; i++) v[i] = __ldg(src + i * 8);
                float s = 0.f;
#pragma unroll
                for (int i = 0; i < 7; i++) {
                    s += (bf_lo(v[i].x) + bf_hi(v[i].x)) + (bf_lo(v[i].y) + bf_hi(v[i].y));
                    s += (bf_lo(v[i].z) + bf_hi(v[i].z)) + (bf_lo(v[i].w) + bf_hi(v[i].w));
                }
                s += __shfl_xor_sync(0xffffffffu, s, 1);
                s += __shfl_xor_sync(0xffffffffu, s, 2);
                s += __shfl_xor_sync(0xffffffffu, s, 4);
                const float mean = s * (1.0f / D_);
                float q = 0.f;
#pragma unroll
                for (int i = 0; i < 7; i++) {
                    const uint32_t w[4] = {v[i].x, v[i].y, v[i].z, v[i].w};
#pragma unroll
                    for (int c = 0; c < 4; c++) {
                        float d0 = bf_lo(w[c]) - mean, d1 = bf_hi(w[c]) - mean;
                        q = fmaf(d0, d0, q);
                        q = fmaf(d1, d1, q);
                    }
                }
                q += __shfl_xor_sync(0xffffffffu, q, 1);
                q += __shfl_xor_sync(0xffffffffu, q, 2);
                q += __shfl_xor_sync(0xffffffffu, q, 4);
                const float mb = rbf(mean);
                const float var = rbf(q * (1.0f / D_));
                const float den = rbf(sqrtf(rbf(var + 1e-5f)));
                const float rinv = 1.0f / den;
                const uint32_t dst = sb + KA_XN + row * 128 + ((l8 ^ (row & 7)) << 4);
#pragma unroll
                for (int i = 0; i < 7; i++) {
                    const uint32_t w[4] = {v[i].x, v[i].y, v[i].z, v[i].w};
                    uint32_t o[4];
#pragma unroll
                    for (int c = 0; c < 4; c++) {
                        uint32_t xc = pack_bf16(bf_lo(w[c]) - mb, bf_hi(w[c]) - mb);
                        o[c] = pack_bf16(bf_lo(xc) * rinv, bf_hi(xc) * rinv);
                    }
                    asm volatile("st.shared.v4.b32 [%0], {%1, %2, %3, %4};" ::"r"(dst + i * 16384), "r"(o[0]), "r"(o[1]), "r"(o[2]), "r"(o[3]) : "memory");
                }
            }
            fence_async();
            bar_sync(1, 256);
        }
        const int wg = warp >> 2, wl = warp & 3, wtid = tid & 127;
        const uint32_t stg = sb + KA_STG + wg * 16384;
        float acc[2][64];
        for (int p = wg; p < npass; p += 2) {
            int type, atom;
            ka_pass(j, p, type, atom);
            int idx = p * 7;
            for (int kb = 0; kb < 7; kb++, idx++) {
                const int st = idx % KA_STAGES;
                const uint32_t ph = (idx / KA_STAGES) & 1;
                mbar_wait(bar_full + 8 * st, ph);
                const uint32_t bs = sb + KA_B + st * 16384;
                const uint32_t as = sb + KA_XN + kb * 16384;
                wg_arrive();
                if (type == P_H) {
#pragma unroll
                    for (int s = 0; s < 4; s++) {
                        const uint64_t db = mkdesc(bs + s * 2048, 8192, 1024);
                        wgmma_n128<1>(acc[0], mkdesc(as + s * 32, 16, 1024), db, kb | s);
                        wgmma_n128<1>(acc[1], mkdesc(as + 8192 + s * 32, 16, 1024), db, kb | s);
                    }
                } else if (type == P_AB128) {
#pragma unroll
                    for (int s = 0; s < 4; s++) {
                        const uint64_t db = mkdesc(bs + s * 32, 16, 1024);
                        wgmma_n128<0>(acc[0], mkdesc(as + s * 32, 16, 1024), db, kb | s);
                        wgmma_n128<0>(acc[1], mkdesc(as + 8192 + s * 32, 16, 1024), db, kb | s);
                    }
                } else {
#pragma unroll
                    for (int s = 0; s < 4; s++) {
                        const uint64_t db = mkdesc(bs + s * 32, 16, 1024);
                        wgmma_n64<0>(acc[0], mkdesc(as + s * 32, 16, 1024), db, kb | s);
                        wgmma_n64<0>(acc[1], mkdesc(as + 8192 + s * 32, 16, 1024), db, kb | s);
                    }
                }
                wg_commit();
                if (kb > 0) {
                    wg_wait<1>();
                    if (lane == 0) mbar_arrive_both(bar_empty + 8 * ((idx - 1) % KA_STAGES));
                }
            }
            wg_wait<0>();
            if (lane == 0) mbar_arrive_both(bar_empty + 8 * ((idx - 1) % KA_STAGES));

            if (type == P_H) {
                if (wtid == 0) bulk_wait_read0();
                bar_sync(2 + wg, 128);
#pragma unroll
                for (int mh = 0; mh < 2; mh++) {
                    const int row = mh * 64 + wl * 16 + (lane & 7) + ((lane >> 3) & 1) * 8;
#pragma unroll
                    for (int jj = 0; jj < 8; jj += 2) {
                        uint32_t r[4];
#pragma unroll
                        for (int t = 0; t < 4; t++) {
                            const int o = (jj + (t >> 1)) * 4 + (t & 1) * 2;
                            const uint32_t g2 = pack_bf16(acc[mh][o], acc[mh][o + 1]);
                            const uint32_t u2 = pack_bf16(acc[mh][32 + o], acc[mh][32 + o + 1]);
                            const uint32_t a2 = pack_bf16(gelu_tanh(bf_lo(g2)), gelu_tanh(bf_hi(g2)));
                            r[t] = pack_bf16(bf_lo(a2) * bf_lo(u2), bf_hi(a2) * bf_hi(u2));
                        }
                        const int chunk = jj + (lane >> 4);
                        stmat4(stg + row * 128 + ((chunk ^ (row & 7)) << 4), r[0], r[1], r[2], r[3]);
                    }
                }
                fence_async();
                bar_sync(2 + wg, 128);
                if (wtid == 0) { tma_store(&tm_h, stg, atom * 64, rb * 128); bulk_commit(); }
            } else {
                const int nh = (type == P_AB128) ? 2 : 1;
#pragma unroll
                for (int hf = 0; hf < 2; hf++) {
                    if (hf < nh) {
                        const int a = atom + hf;
                        const float sgn = (a < 7) ? 1.0f : -1.0f;
                        if (wtid == 0) bulk_wait_read0();
                        bar_sync(2 + wg, 128);
#pragma unroll
                        for (int mh = 0; mh < 2; mh++) {
#pragma unroll
                            for (int jj = 0; jj < 8; jj += 2) {
                                uint32_t r[4];
#pragma unroll
                                for (int t = 0; t < 4; t++) {
                                    const int o = hf * 32 + (jj + (t >> 1)) * 4 + (t & 1) * 2;
                                    r[t] = pack_bf16(sgn * acc[mh][o], sgn * acc[mh][o + 1]);
                                }
                                const int e = 8 * (jj + (lane >> 4)) + (lane & 7);
                                const int sc = 2 * wl + ((lane >> 3) & 1);
                                stmat4t(stg + mh * 8192 + e * 128 + ((sc ^ (e & 7)) << 4), r[0], r[1], r[2], r[3]);
                            }
                        }
                        fence_async();
                        bar_sync(2 + wg, 128);
                        if (wtid == 0) {
                            tma_store(&tm_abT_st, stg, rb * 128, a * 64);
                            tma_store(&tm_abT_st, stg + 8192, rb * 128 + 64, a * 64);
                            bulk_commit();
                        }
                    }
                }
            }
        }
        if (wtid == 0) bulk_wait0();
    }
    cluster_sync();
}

constexpr int KB_STAGES = 4;
constexpr int KB_STAGE = 49152;
constexpr int KB_BAR = KB_STAGES * KB_STAGE;
constexpr int KB_SMEM = KB_BAR + 128 + 1024;
constexpr int KB_NKB = 23;

__device__ __forceinline__ void store_partial(const float (&acc)[112], int tile, int slot, int ctid) {
    float4* dst = g_part + (size_t)(tile * 5 + slot) * (4 * 7 * 256) + ctid;
#pragma unroll
    for (int q = 0; q < 28; q++)
        __stcg(dst + q * 256, make_float4(acc[4 * q], acc[4 * q + 1], acc[4 * q + 2], acc[4 * q + 3]));
}

__global__ void __launch_bounds__(288, 1)
kernel_b(const __nv_bfloat16* __restrict__ x, __nv_bfloat16* __restrict__ out,
         const __grid_constant__ CUtensorMap tm_sre, const __grid_constant__ CUtensorMap tm_sim,
         const __grid_constant__ CUtensorMap tm_h, const __grid_constant__ CUtensorMap tm_abT,
         const __grid_constant__ CUtensorMap tm_wd) {
    extern __shared__ unsigned char smem_raw[];
    const uint32_t sb = (s2u(smem_raw) + 1023) & ~1023u;
    const int tid = threadIdx.x, warp = tid >> 5, lane = tid & 31;
    const int rank = blockIdx.x & 1;
    const int cid = blockIdx.x >> 1;
    const int ks = cid & 3, n = (cid >> 2) & 1, m = (cid >> 3) * 2 + rank;
    const int tile = m * 2 + n;
    const uint32_t bar_full = sb + KB_BAR, bar_empty = sb + KB_BAR + 64;

    if (tid == 0) {
        for (int i = 0; i < KB_STAGES; i++) { mbar_init(bar_full + 8 * i, 1); mbar_init(bar_empty + 8 * i, 16); }
        asm volatile("fence.mbarrier_init.release.cluster;" ::: "memory");
    }
    cluster_sync();
    asm volatile("griddepcontrol.wait;" ::: "memory");

    if (warp == 8) {
        if (lane == 0) {
            for (int i = 0; i < KB_NKB; i++) {
                const int g = ks * KB_NKB + i;
                const int st = i % KB_STAGES;
                const uint32_t ph = (i / KB_STAGES) & 1;
                mbar_wait_cl(bar_empty + 8 * st, ph ^ 1);
                const uint32_t dst = sb + st * KB_STAGE;
                const uint32_t fb = bar_full + 8 * st;
                if (g < 64) {
                    mbar_expect(fb, 16384 + 28672);
                    const int kc = (g & 31) * 64;
                    tma_load(dst, g < 32 ? &tm_sre : &tm_sim, fb, kc, m * 128);
                    tma_load_mc(dst + 16384 + rank * 14336, &tm_abT, fb, kc, (g < 32 ? 0 : 448) + n * 224 + rank * 112);
                } else {
                    mbar_expect(fb, 16384 + 32768);
                    const int kc = (g - 64) * 64;
                    tma_load(dst, &tm_h, fb, kc, m * 128);
                    tma_load_mc(dst + 16384 + (2 * rank) * 8192, &tm_wd, fb, n * 224 + (2 * rank) * 64, kc);
                    tma_load_mc(dst + 16384 + (2 * rank + 1) * 8192, &tm_wd, fb, n * 224 + (2 * rank + 1) * 64, kc);
                }
            }
        }
    } else {
        const int wg = warp >> 2, wl = warp & 3;
        float acc[112];
        int fresh = 1;
        for (int i = 0; i < KB_NKB; i++) {
            const int g = ks * KB_NKB + i;
            const int st = i % KB_STAGES;
            const uint32_t ph = (i / KB_STAGES) & 1;
            if (g == 64 && i > 0) {
                wg_wait<0>();
                store_partial(acc, tile, 2, tid);
                fresh = 1;
            }
            mbar_wait(bar_full + 8 * st, ph);
            const uint32_t as = sb + st * KB_STAGE + wg * 8192;
            const uint32_t bs = sb + st * KB_STAGE + 16384;
            wg_arrive();
            if (g < 64) {
#pragma unroll
                for (int s = 0; s < 4; s++)
                    wgmma_n224<0>(acc, mkdesc(as + s * 32, 16, 1024), mkdesc(bs + s * 32, 16, 1024), (fresh ^ 1) | s);
            } else {
#pragma unroll
                for (int s = 0; s < 4; s++)
                    wgmma_n224<1>(acc, mkdesc(as + s * 32, 16, 1024), mkdesc(bs + s * 2048, 8192, 1024), (fresh ^ 1) | s);
            }
            wg_commit();
            fresh = 0;
            if (i > 0) {
                wg_wait<1>();
                if (lane == 0) mbar_arrive_both(bar_empty + 8 * ((i - 1) % KB_STAGES));
            }
        }
        wg_wait<0>();
        store_partial(acc, tile, ks < 2 ? ks : ks + 1, tid);
        __threadfence();
        bar_sync(1, 256);
        if (tid == 0) {
            atomicAdd(&g_cnt[tile], 1u);
            unsigned v;
            int spins = 0;
            do {
                asm volatile("ld.acquire.gpu.global.u32 %0, [%1];" : "=r"(v) : "l"(&g_cnt[tile]) : "memory");
            } while (v < 4u && ++spins < (1 << 24));
        }
        bar_sync(1, 256);
        const float4* src = g_part + (size_t)(tile * 5) * (4 * 7 * 256) + (ks * 7) * 256 + tid;
        const int row0 = m * 128 + wg * 64 + wl * 16 + (lane >> 2);
        const int col0 = n * 224 + ks * 56 + (lane & 3) * 2;
#pragma unroll
        for (int q = 0; q < 7; q++) {
            const float4 y0 = __ldcg(src + q * 256);
            const float4 y1 = __ldcg(src + q * 256 + 1 * 7168);
            const float4 y2 = __ldcg(src + q * 256 + 2 * 7168);
            const float4 f0 = __ldcg(src + q * 256 + 3 * 7168);
            const float4 f1 = __ldcg(src + q * 256 + 4 * 7168);
            const float yv[4] = {y0.x + y1.x + y2.x, y0.y + y1.y + y2.y, y0.z + y1.z + y2.z, y0.w + y1.w + y2.w};
            const float fv[4] = {f0.x + f1.x, f0.y + f1.y, f0.z + f1.z, f0.w + f1.w};
#pragma unroll
            for (int hh = 0; hh < 2; hh++) {
                const size_t off = (size_t)(row0 + hh * 8) * D_ + col0 + q * 8;
                const uint32_t xv = __ldg(reinterpret_cast<const unsigned int*>(x + off));
                float o[2];
#pragma unroll
                for (int c = 0; c < 2; c++) {
                    const float f = rbf(fv[hh * 2 + c]);
                    const float gg = rbf(f / (1.0f + __expf(-f)));
                    const float sg = rbf(rbf(yv[hh * 2 + c]) * gg);
                    o[c] = (c ? bf_hi(xv) : bf_lo(xv)) + sg;
                }
                *reinterpret_cast<unsigned int*>(out + off) = pack_bf16(o[0], o[1]);
            }
        }
    }
    cluster_sync();
}

typedef CUresult (*EncFn)(CUtensorMap*, CUtensorMapDataType, cuuint32_t, void*, const cuuint64_t*, const cuuint64_t*,
                          const cuuint32_t*, const cuuint32_t*, CUtensorMapInterleave, CUtensorMapSwizzle,
                          CUtensorMapL2promotion, CUtensorMapFloatOOBfill);

void make_map(EncFn enc, CUtensorMap* m, const void* ptr, int rows, int cols, int box_rows, int box_cols) {
    cuuint64_t gd[2] = {(cuuint64_t)cols, (cuuint64_t)rows};
    cuuint64_t gs[1] = {(cuuint64_t)cols * 2};
    cuuint32_t bx[2] = {(cuuint32_t)box_cols, (cuuint32_t)box_rows};
    cuuint32_t es[2] = {1, 1};
    enc(m, CU_TENSOR_MAP_DATA_TYPE_BFLOAT16, 2, const_cast<void*>(ptr), gd, gs, bx, es, CU_TENSOR_MAP_INTERLEAVE_NONE,
        CU_TENSOR_MAP_SWIZZLE_128B, CU_TENSOR_MAP_L2_PROMOTION_L2_128B, CU_TENSOR_MAP_FLOAT_OOB_FILL_NONE);
}

}

extern "C" void kernel_launch(void* const* d_in, const int* in_sizes, int n_in, void* d_out, int out_size) {
    const __nv_bfloat16* x = (const __nv_bfloat16*)d_in[0];
    const __nv_bfloat16* sre = (const __nv_bfloat16*)d_in[1];
    const __nv_bfloat16* sim = (const __nv_bfloat16*)d_in[2];
    const __nv_bfloat16* hre = (const __nv_bfloat16*)d_in[3];
    const __nv_bfloat16* him = (const __nv_bfloat16*)d_in[4];
    const __nv_bfloat16* wgt = (const __nv_bfloat16*)d_in[6];
    const __nv_bfloat16* wup = (const __nv_bfloat16*)d_in[7];
    const __nv_bfloat16* wdn = (const __nv_bfloat16*)d_in[8];
    __nv_bfloat16* out = (__nv_bfloat16*)d_out;

    void* fn = nullptr;
    cudaDriverEntryPointQueryResult qr;
    cudaGetDriverEntryPoint("cuTensorMapEncodeTiled", &fn, cudaEnableDefault, &qr);
    EncFn enc = (EncFn)fn;
    void *p_abT, *p_h;
    cudaGetSymbolAddress(&p_abT, g_abT);
    cudaGetSymbolAddress(&p_h, g_h);

    CUtensorMap tm_wg, tm_wu, tm_hre, tm_him, tm_h, tm_abT_st, tm_abT, tm_sre, tm_sim, tm_wd;
    make_map(enc, &tm_wg, wgt, D_, F_, 64, 64);
    make_map(enc, &tm_wu, wup, D_, F_, 64, 64);
    make_map(enc, &tm_hre, hre, D_, D_, 64, 64);
    make_map(enc, &tm_him, him, D_, D_, 64, 64);
    make_map(enc, &tm_h, p_h, S_, F_, 128, 64);
    make_map(enc, &tm_abT_st, p_abT, 896, S_, 64, 64);
    make_map(enc, &tm_abT, p_abT, 896, S_, 112, 64);
    make_map(enc, &tm_sre, sre, S_, S_, 128, 64);
    make_map(enc, &tm_sim, sim, S_, S_, 128, 64);
    make_map(enc, &tm_wd, wdn, F_, D_, 64, 64);

    cudaFuncSetAttribute(kernel_a, cudaFuncAttributeMaxDynamicSharedMemorySize, KA_SMEM);
    cudaFuncSetAttribute(kernel_b, cudaFuncAttributeMaxDynamicSharedMemorySize, KB_SMEM);

    cudaLaunchAttribute at[2];
    at[0].id = cudaLaunchAttributeClusterDimension;
    at[0].val.clusterDim.x = 2; at[0].val.clusterDim.y = 1; at[0].val.clusterDim.z = 1;
    at[1].id = cudaLaunchAttributeProgrammaticStreamSerialization;
    at[1].val.programmaticStreamSerializationAllowed = 1;

    cudaLaunchConfig_t cfg = {};
    cfg.gridDim = dim3(128); cfg.blockDim = dim3(288); cfg.stream = cudaStreamPerThread;
    cfg.attrs = at;
    cfg.dynamicSmemBytes = KA_SMEM; cfg.numAttrs = 1;
    cudaLaunchKernelEx(&cfg, kernel_a, x, tm_wg, tm_wu, tm_hre, tm_him, tm_h, tm_abT_st, sre, sim);
    cfg.dynamicSmemBytes = KB_SMEM; cfg.numAttrs = 2;
    cudaLaunchKernelEx(&cfg, kernel_b, x, out, tm_sre, tm_sim, tm_h, tm_abT, tm_wd);
}
```

```cpp
#include <cuda_runtime.h>
#include <cuda_bf16.h>
#include <cuda.h>
#include <stdint.h>

namespace {

constexpr int S_ = 2048, D_ = 448, F_ = 1792;

__device__ __align__(1024) __nv_bfloat16 g_abT[896 * 2048];
__device__ __align__(1024) __nv_bfloat16 g_h[2048 * 1792];
__device__ __align__(1024) float4 g_part[32 * 5 * 4 * 7 * 256];
__device__ unsigned int g_cnt[32];

__device__ __forceinline__ uint32_t s2u(const void* p) { return (uint32_t)__cvta_generic_to_shared(p); }
__device__ __forceinline__ void mbar_init(uint32_t b, int c) {
    asm volatile("mbarrier.init.shared::cta.b64 [%0], %1;" ::"r"(b), "r"(c));
}
__device__ __forceinline__ void mbar_expect(uint32_t b, uint32_t bytes) {
    asm volatile("mbarrier.arrive.expect_tx.shared::cta.b64 _, [%0], %1;" ::"r"(b), "r"(bytes) : "memory");
}
__device__ __forceinline__ void mbar_wait(uint32_t b, uint32_t ph) {
    uint32_t ok;
    do {
        asm volatile("{\n.reg .pred p;\nmbarrier.try_wait.parity.shared::cta.b64 p, [%1], %2;\nselp.u32 %0, 1, 0, p;\n}"
                     : "=r"(ok) : "r"(b), "r"(ph) : "memory");
    } while (!ok);
}
__device__ __forceinline__ void mbar_wait_cl(uint32_t b, uint32_t ph) {
    uint32_t ok;
    do {
        asm volatile("{\n.reg .pred p;\nmbarrier.try_wait.parity.acquire.cluster.shared::cta.b64 p, [%1], %2;\nselp.u32 %0, 1, 0, p;\n}"
                     : "=r"(ok) : "r"(b), "r"(ph) : "memory");
    } while (!ok);
}
__device__ __forceinline__ void mbar_arrive_both(uint32_t b) {
    asm volatile("{\n.reg .b32 r0, r1;\n"
                 "mapa.shared::cluster.u32 r0, %0, 0;\n"
                 "mapa.shared::cluster.u32 r1, %0, 1;\n"
                 "mbarrier.arrive.shared::cluster.b64 _, [r0];\n"
                 "mbarrier.arrive.shared::cluster.b64 _, [r1];\n}"
                 ::"r"(b) : "memory");
}
__device__ __forceinline__ void tma_load(uint32_t dst, const CUtensorMap* m, uint32_t bar, int c0, int c1) {
    asm volatile("cp.async.bulk.tensor.2d.shared::cluster.global.mbarrier::complete_tx::bytes [%0], [%1, {%3, %4}], [%2];"
                 ::"r"(dst), "l"(m), "r"(bar), "r"(c0), "r"(c1) : "memory");
}
__device__ __forceinline__ void tma_load_mc(uint32_t dst, const CUtensorMap* m, uint32_t bar, int c0, int c1) {
    asm volatile("cp.async.bulk.tensor.2d.shared::cluster.global.mbarrier::complete_tx::bytes.multicast::cluster [%0], [%1, {%3, %4}], [%2], %5;"
                 ::"r"(dst), "l"(m), "r"(bar), "r"(c0), "r"(c1), "h"((uint16_t)3) : "memory");
}
__device__ __forceinline__ void tma_store(const CUtensorMap* m, uint32_t src, int c0, int c1) {
    asm volatile("cp.async.bulk.tensor.2d.global.shared::cta.bulk_group [%0, {%2, %3}], [%1];"
                 ::"l"(m), "r"(src), "r"(c0), "r"(c1) : "memory");
}
__device__ __forceinline__ void bulk_commit() { asm volatile("cp.async.bulk.commit_group;" ::: "memory"); }
__device__ __forceinline__ void bulk_wait_read0() { asm volatile("cp.async.bulk.wait_group.read 0;" ::: "memory"); }
__device__ __forceinline__ void bulk_wait0() { asm volatile("cp.async.bulk.wait_group 0;" ::: "memory"); }
__device__ __forceinline__ void fence_async() { asm volatile("fence.proxy.async.shared::cta;" ::: "memory"); }
__device__ __forceinline__ void cluster_sync() {
    asm volatile("barrier.cluster.arrive.release.aligned;\nbarrier.cluster.wait.acquire.aligned;" ::: "memory");
}
__device__ __forceinline__ void bar_sync(int id, int n) { asm volatile("bar.sync %0, %1;" ::"r"(id), "r"(n) : "memory"); }
__device__ __forceinline__ void wg_arrive() { asm volatile("wgmma.fence.sync.aligned;" ::: "memory"); }
__device__ __forceinline__ void wg_commit() { asm volatile("wgmma.commit_group.sync.aligned;" ::: "memory"); }
template <int N> __device__ __forceinline__ void wg_wait() { asm volatile("wgmma.wait_group.sync.aligned %0;" ::"n"(N) : "memory"); }
__device__ __forceinline__ void prefetch_tmap(const CUtensorMap* m) {
    asm volatile("prefetch.tensormap [%0];" ::"l"(m) : "memory");
}
__device__ __forceinline__ void stmat4(uint32_t a, uint32_t r0, uint32_t r1, uint32_t r2, uint32_t r3) {
    asm volatile("stmatrix.sync.aligned.m8n8.x4.shared.b16 [%0], {%1, %2, %3, %4};" ::"r"(a), "r"(r0), "r"(r1), "r"(r2), "r"(r3) : "memory");
}
__device__ __forceinline__ void stmat4t(uint32_t a, uint32_t r0, uint32_t r1, uint32_t r2, uint32_t r3) {
    asm volatile("stmatrix.sync.aligned.m8n8.x4.trans.shared.b16 [%0], {%1, %2, %3, %4};" ::"r"(a), "r"(r0), "r"(r1), "r"(r2), "r"(r3) : "memory");
}
__device__ __forceinline__ uint64_t mkdesc(uint32_t addr, uint32_t lbo, uint32_t sbo) {
    return (uint64_t)((addr & 0x3FFFF) >> 4) | ((uint64_t)(lbo >> 4) << 16) | ((uint64_t)(sbo >> 4) << 32) | (1ull << 62);
}
__device__ __forceinline__ uint32_t pack_bf16(float lo, float hi) {
    uint32_t r;
    asm("cvt.rn.bf16x2.f32 %0, %1, %2;" : "=r"(r) : "f"(hi), "f"(lo));
    return r;
}
__device__ __forceinline__ float bf_lo(uint32_t u) { return __uint_as_float(u << 16); }
__device__ __forceinline__ float bf_hi(uint32_t u) { return __uint_as_float(u & 0xffff0000u); }
__device__ __forceinline__ float rbf(float v) { return __bfloat162float(__float2bfloat16_rn(v)); }
__device__ __forceinline__ float tanh_fast(float x) { float r; asm("tanh.approx.f32 %0, %1;" : "=f"(r) : "f"(x)); return r; }
__device__ __forceinline__ float gelu_tanh(float x) {
    float u = x * fmaf(x * x, 0.0356774081f, 0.7978845608f);
    float hx = 0.5f * x;
    return fmaf(hx, tanh_fast(u), hx);
}

template <int TB>
__device__ __forceinline__ void wgmma_n64(float (&d)[64], uint64_t da, uint64_t db, int scaleD) {
    asm volatile("{\n.reg .pred p;\nsetp.ne.b32 p, %34, 0;\n"
        "wgmma.mma_async.sync.aligned.m64n64k16.f32.bf16.bf16 {%0, %1, %2, %3, %4, %5, %6, %7, %8, %9, %10, %11, %12, %13, %14, %15, %16, %17, %18, %19, %20, %21, %22, %23, %24, %25, %26, %27, %28, %29, %30, %31}, %32, %33, p, 1, 1, 0, %35;\n}\n"
        : "+f"(d[0]), "+f"(d[1]), "+f"(d[2]), "+f"(d[3]), "+f"(d[4]), "+f"(d[5]), "+f"(d[6]), "+f"(d[7]), "+f"(d[8]), "+f"(d[9]), "+f"(d[10]), "+f"(d[11]), "+f"(d[12]), "+f"(d[13]), "+f"(d[14]), "+f"(d[15]), "+f"(d[16]), "+f"(d[17]), "+f"(d[18]), "+f"(d[19]), "+f"(d[20]), "+f"(d[21]), "+f"(d[22]), "+f"(d[23]), "+f"(d[24]), "+f"(d[25]), "+f"(d[26]), "+f"(d[27]), "+f"(d[28]), "+f"(d[29]), "+f"(d[30]), "+f"(d[31])
        : "l"(da), "l"(db), "r"(scaleD), "n"(TB));
}
template <int TB>
__device__ __forceinline__ void wgmma_n128(float (&d)[64], uint64_t da, uint64_t db, int scaleD) {
    asm volatile("{\n.reg .pred p;\nsetp.ne.b32 p, %66, 0;\n"
        "wgmma.mma_async.sync.aligned.m64n128k16.f32.bf16.bf16 {%0, %1, %2, %3, %4, %5, %6, %7, %8, %9, %10, %11, %12, %13, %14, %15, %16, %17, %18, %19, %20, %21, %22, %23, %24, %25, %26, %27, %28, %29, %30, %31, %32, %33, %34, %35, %36, %37, %38, %39, %40, %41, %42, %43, %44, %45, %46, %47, %48, %49, %50, %51, %52, %53, %54, %55, %56, %57, %58, %59, %60, %61, %62, %63}, %64, %65, p, 1, 1, 0, %67;\n}\n"
        : "+f"(d[0]), "+f"(d[1]), "+f"(d[2]), "+f"(d[3]), "+f"(d[4]), "+f"(d[5]), "+f"(d[6]), "+f"(d[7]), "+f"(d[8]), "+f"(d[9]), "+f"(d[10]), "+f"(d[11]), "+f"(d[12]), "+f"(d[13]), "+f"(d[14]), "+f"(d[15]), "+f"(d[16]), "+f"(d[17]), "+f"(d[18]), "+f"(d[19]), "+f"(d[20]), "+f"(d[21]), "+f"(d[22]), "+f"(d[23]), "+f"(d[24]), "+f"(d[25]), "+f"(d[26]), "+f"(d[27]), "+f"(d[28]), "+f"(d[29]), "+f"(d[30]), "+f"(d[31]), "+f"(d[32]), "+f"(d[33]), "+f"(d[34]), "+f"(d[35]), "+f"(d[36]), "+f"(d[37]), "+f"(d[38]), "+f"(d[39]), "+f"(d[40]), "+f"(d[41]), "+f"(d[42]), "+f"(d[43]), "+f"(d[44]), "+f"(d[45]), "+f"(d[46]), "+f"(d[47]), "+f"(d[48]), "+f"(d[49]), "+f"(d[50]), "+f"(d[51]), "+f"(d[52]), "+f"(d[53]), "+f"(d[54]), "+f"(d[55]), "+f"(d[56]), "+f"(d[57]), "+f"(d[58]), "+f"(d[59]), "+f"(d[60]), "+f"(d[61]), "+f"(d[62]), "+f"(d[63])
        : "l"(da), "l"(db), "r"(scaleD), "n"(TB));
}
template <int TB>
__device__ __forceinline__ void wgmma_n224(float (&d)[112], uint64_t da, uint64_t db, int scaleD) {
    asm volatile("{\n.reg .pred p;\nsetp.ne.b32 p, %114, 0;\n"
        "wgmma.mma_async.sync.aligned.m64n224k16.f32.bf16.bf16 {%0, %1, %2, %3, %4, %5, %6, %7, %8, %9, %10, %11, %12, %13, %14, %15, %16, %17, %18, %19, %20, %21, %22, %23, %24, %25, %26, %27, %28, %29, %30, %31, %32, %33, %34, %35, %36, %37, %38, %39, %40, %41, %42, %43, %44, %45, %46, %47, %48, %49, %50, %51, %52, %53, %54, %55, %56, %57, %58, %59, %60, %61, %62, %63, %64, %65, %66, %67, %68, %69, %70, %71, %72, %73, %74, %75, %76, %77, %78, %79, %80, %81, %82, %83, %84, %85, %86, %87, %88, %89, %90, %91, %92, %93, %94, %95, %96, %97, %98, %99, %100, %101, %102, %103, %104, %105, %106, %107, %108, %109, %110, %111}, %112, %113, p, 1, 1, 0, %115;\n}\n"
        : "+f"(d[0]), "+f"(d[1]), "+f"(d[2]), "+f"(d[3]), "+f"(d[4]), "+f"(d[5]), "+f"(d[6]), "+f"(d[7]), "+f"(d[8]), "+f"(d[9]), "+f"(d[10]), "+f"(d[11]), "+f"(d[12]), "+f"(d[13]), "+f"(d[14]), "+f"(d[15]), "+f"(d[16]), "+f"(d[17]), "+f"(d[18]), "+f"(d[19]), "+f"(d[20]), "+f"(d[21]), "+f"(d[22]), "+f"(d[23]), "+f"(d[24]), "+f"(d[25]), "+f"(d[26]), "+f"(d[27]), "+f"(d[28]), "+f"(d[29]), "+f"(d[30]), "+f"(d[31]), "+f"(d[32]), "+f"(d[33]), "+f"(d[34]), "+f"(d[35]), "+f"(d[36]), "+f"(d[37]), "+f"(d[38]), "+f"(d[39]), "+f"(d[40]), "+f"(d[41]), "+f"(d[42]), "+f"(d[43]), "+f"(d[44]), "+f"(d[45]), "+f"(d[46]), "+f"(d[47]), "+f"(d[48]), "+f"(d[49]), "+f"(d[50]), "+f"(d[51]), "+f"(d[52]), "+f"(d[53]), "+f"(d[54]), "+f"(d[55]), "+f"(d[56]), "+f"(d[57]), "+f"(d[58]), "+f"(d[59]), "+f"(d[60]), "+f"(d[61]), "+f"(d[62]), "+f"(d[63]), "+f"(d[64]), "+f"(d[65]), "+f"(d[66]), "+f"(d[67]), "+f"(d[68]), "+f"(d[69]), "+f"(d[70]), "+f"(d[71]), "+f"(d[72]), "+f"(d[73]), "+f"(d[74]), "+f"(d[75]), "+f"(d[76]), "+f"(d[77]), "+f"(d[78]), "+f"(d[79]), "+f"(d[80]), "+f"(d[81]), "+f"(d[82]), "+f"(d[83]), "+f"(d[84]), "+f"(d[85]), "+f"(d[86]), "+f"(d[87]), "+f"(d[88]), "+f"(d[89]), "+f"(d[90]), "+f"(d[91]), "+f"(d[92]), "+f"(d[93]), "+f"(d[94]), "+f"(d[95]), "+f"(d[96]), "+f"(d[97]), "+f"(d[98]), "+f"(d[99]), "+f"(d[100]), "+f"(d[101]), "+f"(d[102]), "+f"(d[103]), "+f"(d[104]), "+f"(d[105]), "+f"(d[106]), "+f"(d[107]), "+f"(d[108]), "+f"(d[109]), "+f"(d[110]), "+f"(d[111])
        : "l"(da), "l"(db), "r"(scaleD), "n"(TB));
}


constexpr int KA_STAGES = 5;
constexpr int KA_XN = 0;
constexpr int KA_B = 7 * 16384;
constexpr int KA_STG = KA_B + KA_STAGES * 16384;
constexpr int KA_BAR = KA_STG + 2 * 16384;
constexpr int KA_SMEM = KA_BAR + 128 + 1024;

enum { P_H = 0, P_AB128 = 1, P_AB64 = 2 };
__device__ __forceinline__ void ka_pass(int j, int p, int& type, int& atom) {
    if (j < 7) {
        if (p < 4) { type = P_H; atom = 4 * j + p; } else { type = P_AB64; atom = j; }
    } else {
        if (p < 3) { type = P_AB128; atom = 7 + 2 * p; } else { type = P_AB64; atom = 13; }
    }
}

template <int TYPE>
__device__ __forceinline__ void ka_mainloop(float (&acc)[2][64], uint32_t sb, int idx, int lane, int handoff) {
    const uint32_t bar_full = sb + KA_BAR, bar_empty = sb + KA_BAR + 64;
    int st = idx % KA_STAGES;
    uint32_t ph = (idx / KA_STAGES) & 1;
    int prev = 0;
#pragma unroll 1
    for (int kb = 0; kb < 7; kb++) {
        mbar_wait(bar_full + 8 * st, ph);
        if (kb == 6 && handoff) asm volatile("bar.arrive %0, 256;" ::"r"(handoff) : "memory");
        const uint32_t bs = sb + KA_B + st * 16384;
        const uint32_t as = sb + KA_XN + kb * 16384;
        wg_arrive();
#pragma unroll
        for (int s = 0; s < 4; s++) {
            const uint64_t da0 = mkdesc(as + s * 32, 16, 1024), da1 = mkdesc(as + 8192 + s * 32, 16, 1024);
            if (TYPE == P_H) {
                const uint64_t db = mkdesc(bs + s * 2048, 8192, 1024);
                wgmma_n128<1>(acc[0], da0, db, kb | s);
                wgmma_n128<1>(acc[1], da1, db, kb | s);
            } else if (TYPE == P_AB128) {
                const uint64_t db = mkdesc(bs + s * 32, 16, 1024);
                wgmma_n128<0>(acc[0], da0, db, kb | s);
                wgmma_n128<0>(acc[1], da1, db, kb | s);
            } else {
                const uint64_t db = mkdesc(bs + s * 32, 16, 1024);
                wgmma_n64<0>(acc[0], da0, db, kb | s);
                wgmma_n64<0>(acc[1], da1, db, kb | s);
            }
        }
        wg_commit();
        wg_wait<1>();
        if (kb > 0 && lane == 0) mbar_arrive_both(bar_empty + 8 * prev);
        prev = st;
        if (++st == KA_STAGES) { st = 0; ph ^= 1; }
    }
    wg_wait<0>();
    if (lane == 0) mbar_arrive_both(bar_empty + 8 * prev);
}

__global__ void __launch_bounds__(288, 1)
kernel_a(const __nv_bfloat16* __restrict__ x,
         const __grid_constant__ CUtensorMap tm_wg, const __grid_constant__ CUtensorMap tm_wu,
         const __grid_constant__ CUtensorMap tm_hre, const __grid_constant__ CUtensorMap tm_him,
         const __grid_constant__ CUtensorMap tm_h, const __grid_constant__ CUtensorMap tm_abT_st,
         const __nv_bfloat16* __restrict__ seq_re, const __nv_bfloat16* __restrict__ seq_im) {
    extern __shared__ unsigned char smem_raw[];
    const uint32_t sb = (s2u(smem_raw) + 1023) & ~1023u;
    const int tid = threadIdx.x, warp = tid >> 5, lane = tid & 31;
    const int rank = blockIdx.x & 1;
    const int cid = blockIdx.x >> 1;
    const int j = cid & 7;
    const int rb = (cid >> 3) * 2 + rank;
    const int npass = (j < 7) ? 5 : 4;
    const uint32_t bar_full = sb + KA_BAR, bar_empty = sb + KA_BAR + 64;

    if (tid == 0) {
        for (int i = 0; i < KA_STAGES; i++) { mbar_init(bar_full + 8 * i, 1); mbar_init(bar_empty + 8 * i, 8); }
        asm volatile("fence.mbarrier_init.release.cluster;" ::: "memory");
    }
    if (blockIdx.x == 0 && tid < 32) g_cnt[tid] = 0;
    asm volatile("griddepcontrol.launch_dependents;" ::: "memory");
    cluster_sync();

    if (warp == 8) {
        if (lane == 0) {
            int idx = 0;
            for (int p = 0; p < npass; p++) {
                int type, atom;
                ka_pass(j, p, type, atom);
                for (int kb = 0; kb < 7; kb++, idx++) {
                    const int st = idx % KA_STAGES;
                    const uint32_t ph = (idx / KA_STAGES) & 1;
                    mbar_wait(bar_empty + 8 * st, ph ^ 1);
                    const uint32_t dst = sb + KA_B + st * 16384;
                    const uint32_t fb = bar_full + 8 * st;
                    mbar_expect(fb, type == P_AB64 ? 8192 : 16384);
                    if (type == P_H) {
                        tma_load_mc(dst + rank * 8192, rank ? &tm_wu : &tm_wg, fb, atom * 64, kb * 64);
                    } else if (type == P_AB128) {
                        const int a = atom + rank;
                        tma_load_mc(dst + rank * 8192, a < 7 ? &tm_hre : &tm_him, fb, kb * 64, (a < 7 ? a : a - 7) * 64);
                    } else if (rank == 0) {
                        tma_load_mc(dst, atom < 7 ? &tm_hre : &tm_him, fb, kb * 64, (atom < 7 ? atom : atom - 7) * 64);
                    }
                    if (idx == KA_STAGES - 1) {
                        const char* base = (const char*)((blockIdx.x < 64) ? seq_re : seq_im) + (size_t)(blockIdx.x & 63) * 131072;
                        for (int q = 0; q < 8; q++)
                            asm volatile("cp.async.bulk.prefetch.L2.global [%0], %1;" ::"l"(base + q * 16384), "r"(16384) : "memory");
                    }
                }
            }
        }
        __syncwarp();
    } else {
        {
            const int l8 = lane & 7, sub = lane >> 3;
#pragma unroll 2
            for (int it = 0; it < 4; it++) {
                const int row = warp * 16 + it * 4 + sub;
                const uint4* src = reinterpret_cast<const uint4*>(x + (size_t)(rb * 128 + row) * D_) + l8;
                uint4 v[7];
#pragma unroll
                for (int i = 0; i < 7; i++) v[i] = __ldg(src + i * 8);
                float s = 0.f;
#pragma unroll
                for (int i = 0; i < 7; i++) {
                    s += (bf_lo(v[i].x) + bf_hi(v[i].x)) + (bf_lo(v[i].y) + bf_hi(v[i].y));
                    s += (bf_lo(v[i].z) + bf_hi(v[i].z)) + (bf_lo(v[i].w) + bf_hi(v[i].w));
                }
                s += __shfl_xor_sync(0xffffffffu, s, 1);
                s += __shfl_xor_sync(0xffffffffu, s, 2);
                s += __shfl_xor_sync(0xffffffffu, s, 4);
                const float mean = s * (1.0f / D_);
                float q = 0.f;
#pragma unroll
                for (int i = 0; i < 7; i++) {
                    const uint32_t w[4] = {v[i].x, v[i].y, v[i].z, v[i].w};
#pragma unroll
                    for (int c = 0; c < 4; c++) {
                        float d0 = bf_lo(w[c]) - mean, d1 = bf_hi(w[c]) - mean;
                        q = fmaf(d0, d0, q);
                        q = fmaf(d1, d1, q);
                    }
                }
                q += __shfl_xor_sync(0xffffffffu, q, 1);
                q += __shfl_xor_sync(0xffffffffu, q, 2);
                q += __shfl_xor_sync(0xffffffffu, q, 4);
                const float mb = rbf(mean);
                const float var = rbf(q * (1.0f / D_));
                const float den = rbf(sqrtf(rbf(var + 1e-5f)));
                const float rinv = 1.0f / den;
                const uint32_t dst = sb + KA_XN + row * 128 + ((l8 ^ (row & 7)) << 4);
#pragma unroll
                for (int i = 0; i < 7; i++) {
                    const uint32_t w[4] = {v[i].x, v[i].y, v[i].z, v[i].w};
                    uint32_t o[4];
#pragma unroll
                    for (int c = 0; c < 4; c++) {
                        uint32_t xc = pack_bf16(bf_lo(w[c]) - mb, bf_hi(w[c]) - mb);
                        o[c] = pack_bf16(bf_lo(xc) * rinv, bf_hi(xc) * rinv);
                    }
                    asm volatile("st.shared.v4.b32 [%0], {%1, %2, %3, %4};" ::"r"(dst + i * 16384), "r"(o[0]), "r"(o[1]), "r"(o[2]), "r"(o[3]) : "memory");
                }
            }
            fence_async();
            bar_sync(1, 256);
        }
        const int wg = warp >> 2, wl = warp & 3, wtid = tid & 127;
        const uint32_t stg = sb + KA_STG + wg * 16384;
        float acc[2][64];
        for (int p = wg; p < npass; p += 2) {
            int type, atom;
            ka_pass(j, p, type, atom);
            if (p > 0) bar_sync(4 + (p & 1), 256);
            const int handoff = (p + 1 < npass) ? 4 + ((p + 1) & 1) : 0;
            if (type == P_H) ka_mainloop<P_H>(acc, sb, p * 7, lane, handoff);
            else if (type == P_AB128) ka_mainloop<P_AB128>(acc, sb, p * 7, lane, handoff);
            else ka_mainloop<P_AB64>(acc, sb, p * 7, lane, handoff);

            if (type == P_H) {
                if (wtid == 0) bulk_wait_read0();
                bar_sync(2 + wg, 128);
#pragma unroll
                for (int mh = 0; mh < 2; mh++) {
                    const int row = mh * 64 + wl * 16 + (lane & 7) + ((lane >> 3) & 1) * 8;
#pragma unroll
                    for (int jj = 0; jj < 8; jj += 2) {
                        uint32_t r[4];
#pragma unroll
                        for (int t = 0; t < 4; t++) {
                            const int o = (jj + (t >> 1)) * 4 + (t & 1) * 2;
                            const uint32_t g2 = pack_bf16(acc[mh][o], acc[mh][o + 1]);
                            const uint32_t u2 = pack_bf16(acc[mh][32 + o], acc[mh][32 + o + 1]);
                            const uint32_t a2 = pack_bf16(gelu_tanh(bf_lo(g2)), gelu_tanh(bf_hi(g2)));
                            r[t] = pack_bf16(bf_lo(a2) * bf_lo(u2), bf_hi(a2) * bf_hi(u2));
                        }
                        const int chunk = jj + (lane >> 4);
                        stmat4(stg + row * 128 + ((chunk ^ (row & 7)) << 4), r[0], r[1], r[2], r[3]);
                    }
                }
                fence_async();
                bar_sync(2 + wg, 128);
                if (wtid == 0) { tma_store(&tm_h, stg, atom * 64, rb * 128); bulk_commit(); }
            } else {
                const int nh = (type == P_AB128) ? 2 : 1;
#pragma unroll
                for (int hf = 0; hf < 2; hf++) {
                    if (hf < nh) {
                        const int a = atom + hf;
                        const float sgn = (a < 7) ? 1.0f : -1.0f;
                        if (wtid == 0) bulk_wait_read0();
                        bar_sync(2 + wg, 128);
#pragma unroll
                        for (int mh = 0; mh < 2; mh++) {
#pragma unroll
                            for (int jj = 0; jj < 8; jj += 2) {
                                uint32_t r[4];
#pragma unroll
                                for (int t = 0; t < 4; t++) {
                                    const int o = hf * 32 + (jj + (t >> 1)) * 4 + (t & 1) * 2;
                                    r[t] = pack_bf16(sgn * acc[mh][o], sgn * acc[mh][o + 1]);
                                }
                                const int e = 8 * (jj + (lane >> 4)) + (lane & 7);
                                const int sc = 2 * wl + ((lane >> 3) & 1);
                                stmat4t(stg + mh * 8192 + e * 128 + ((sc ^ (e & 7)) << 4), r[0], r[1], r[2], r[3]);
                            }
                        }
                        fence_async();
                        bar_sync(2 + wg, 128);
                        if (wtid == 0) {
                            tma_store(&tm_abT_st, stg, rb * 128, a * 64);
                            tma_store(&tm_abT_st, stg + 8192, rb * 128 + 64, a * 64);
                            bulk_commit();
                        }
                    }
                }
            }
        }
        if (wtid == 0) bulk_wait0();
    }
    cluster_sync();
}

constexpr int KB_STAGES = 4;
constexpr int KB_STAGE = 49152;
constexpr int KB_BAR = KB_STAGES * KB_STAGE;
constexpr int KB_SMEM = KB_BAR + 128 + 1024;
constexpr int KB_NKB = 23;

__device__ __forceinline__ void store_partial(const float (&acc)[112], int tile, int slot, int ctid) {
    float4* dst = g_part + (size_t)(tile * 5 + slot) * (4 * 7 * 256) + ctid;
#pragma unroll
    for (int q = 0; q < 28; q++)
        __stcg(dst + q * 256, make_float4(acc[4 * q], acc[4 * q + 1], acc[4 * q + 2], acc[4 * q + 3]));
}

template <int TB>
__device__ __forceinline__ void kb_mainloop(float (&acc)[112], uint32_t sb, int i0, int i1, int wg, int lane) {
    const uint32_t bar_full = sb + KB_BAR, bar_empty = sb + KB_BAR + 64;
    int st = i0 % KB_STAGES;
    uint32_t ph = (i0 / KB_STAGES) & 1;
    int prev = 0;
#pragma unroll 1
    for (int i = i0; i < i1; i++) {
        mbar_wait(bar_full + 8 * st, ph);
        const uint32_t as = sb + st * KB_STAGE + wg * 8192;
        const uint32_t bs = sb + st * KB_STAGE + 16384;
        wg_arrive();
#pragma unroll
        for (int s = 0; s < 4; s++) {
            const uint64_t db = TB ? mkdesc(bs + s * 2048, 8192, 1024) : mkdesc(bs + s * 32, 16, 1024);
            wgmma_n224<TB>(acc, mkdesc(as + s * 32, 16, 1024), db, (i - i0) | s);
        }
        wg_commit();
        wg_wait<1>();
        if (i > i0 && lane == 0) mbar_arrive_both(bar_empty + 8 * prev);
        prev = st;
        if (++st == KB_STAGES) { st = 0; ph ^= 1; }
    }
    wg_wait<0>();
    if (lane == 0) mbar_arrive_both(bar_empty + 8 * prev);
}

__global__ void __launch_bounds__(288, 1)
kernel_b(const __nv_bfloat16* __restrict__ x, __nv_bfloat16* __restrict__ out,
         const __grid_constant__ CUtensorMap tm_sre, const __grid_constant__ CUtensorMap tm_sim,
         const __grid_constant__ CUtensorMap tm_h, const __grid_constant__ CUtensorMap tm_abT,
         const __grid_constant__ CUtensorMap tm_wd) {
    extern __shared__ unsigned char smem_raw[];
    const uint32_t sb = (s2u(smem_raw) + 1023) & ~1023u;
    const int tid = threadIdx.x, warp = tid >> 5, lane = tid & 31;
    const int rank = blockIdx.x & 1;
    const int cid = blockIdx.x >> 1;
    const int ks = cid & 3, n = (cid >> 2) & 1, m = (cid >> 3) * 2 + rank;
    const int tile = m * 2 + n;
    const uint32_t bar_full = sb + KB_BAR, bar_empty = sb + KB_BAR + 64;

    if (tid == 0) {
        for (int i = 0; i < KB_STAGES; i++) { mbar_init(bar_full + 8 * i, 1); mbar_init(bar_empty + 8 * i, 16); }
        asm volatile("fence.mbarrier_init.release.cluster;" ::: "memory");
    }
    cluster_sync();
    asm volatile("griddepcontrol.wait;" ::: "memory");

    if (warp == 8) {
        if (lane == 0) {
            for (int i = 0; i < KB_NKB; i++) {
                const int g = ks * KB_NKB + i;
                const int st = i % KB_STAGES;
                const uint32_t ph = (i / KB_STAGES) & 1;
                mbar_wait(bar_empty + 8 * st, ph ^ 1);
                const uint32_t dst = sb + st * KB_STAGE;
                const uint32_t fb = bar_full + 8 * st;
                if (g < 64) {
                    mbar_expect(fb, 16384 + 28672);
                    const int kc = (g & 31) * 64;
                    tma_load(dst, g < 32 ? &tm_sre : &tm_sim, fb, kc, m * 128);
                    tma_load_mc(dst + 16384 + rank * 14336, &tm_abT, fb, kc, (g < 32 ? 0 : 448) + n * 224 + rank * 112);
                } else {
                    mbar_expect(fb, 16384 + 32768);
                    const int kc = (g - 64) * 64;
                    tma_load(dst, &tm_h, fb, kc, m * 128);
                    tma_load_mc(dst + 16384 + (2 * rank) * 8192, &tm_wd, fb, n * 224 + (2 * rank) * 64, kc);
                    tma_load_mc(dst + 16384 + (2 * rank + 1) * 8192, &tm_wd, fb, n * 224 + (2 * rank + 1) * 64, kc);
                }
            }
        }
        __syncwarp();
    } else {
        const int wg = warp >> 2, wl = warp & 3;
        float acc[112];
        const int ny = min(max(64 - ks * KB_NKB, 0), KB_NKB);
        if (ny > 0) kb_mainloop<0>(acc, sb, 0, ny, wg, lane);
        if (ny > 0 && ny < KB_NKB) store_partial(acc, tile, 2, tid);
        if (ny < KB_NKB) kb_mainloop<1>(acc, sb, ny, KB_NKB, wg, lane);
        store_partial(acc, tile, ks < 2 ? ks : ks + 1, tid);
        __threadfence();
        bar_sync(1, 256);
        if (tid == 0) {
            atomicAdd(&g_cnt[tile], 1u);
            unsigned v;
            int spins = 0;
            do {
                asm volatile("ld.acquire.gpu.global.u32 %0, [%1];" : "=r"(v) : "l"(&g_cnt[tile]) : "memory");
            } while (v < 4u && ++spins < (1 << 24));
        }
        bar_sync(1, 256);
        const float4* src = g_part + (size_t)(tile * 5) * (4 * 7 * 256) + (ks * 7) * 256 + tid;
        const int row0 = m * 128 + wg * 64 + wl * 16 + (lane >> 2);
        const int col0 = n * 224 + ks * 56 + (lane & 3) * 2;
#pragma unroll
        for (int q = 0; q < 7; q++) {
            const float4 y0 = __ldcg(src + q * 256);
            const float4 y1 = __ldcg(src + q * 256 + 1 * 7168);
            const float4 y2 = __ldcg(src + q * 256 + 2 * 7168);
            const float4 f0 = __ldcg(src + q * 256 + 3 * 7168);
            const float4 f1 = __ldcg(src + q * 256 + 4 * 7168);
            const float yv[4] = {y0.x + y1.x + y2.x, y0.y + y1.y + y2.y, y0.z + y1.z + y2.z, y0.w + y1.w + y2.w};
            const float fv[4] = {f0.x + f1.x, f0.y + f1.y, f0.z + f1.z, f0.w + f1.w};
#pragma unroll
            for (int hh = 0; hh < 2; hh++) {
                const size_t off = (size_t)(row0 + hh * 8) * D_ + col0 + q * 8;
                const uint32_t xv = __ldg(reinterpret_cast<const unsigned int*>(x + off));
                float o[2];
#pragma unroll
                for (int c = 0; c < 2; c++) {
                    const float f = rbf(fv[hh * 2 + c]);
                    const float gg = rbf(f / (1.0f + __expf(-f)));
                    const float sg = rbf(rbf(yv[hh * 2 + c]) * gg);
                    o[c] = (c ? bf_hi(xv) : bf_lo(xv)) + sg;
                }
                *reinterpret_cast<unsigned int*>(out + off) = pack_bf16(o[0], o[1]);
            }
        }
    }
    cluster_sync();
}

typedef CUresult (*EncFn)(CUtensorMap*, CUtensorMapDataType, cuuint32_t, void*, const cuuint64_t*, const cuuint64_t*,
                          const cuuint32_t*, const cuuint32_t*, CUtensorMapInterleave, CUtensorMapSwizzle,
                          CUtensorMapL2promotion, CUtensorMapFloatOOBfill);

void make_map(EncFn enc, CUtensorMap* m, const void* ptr, int rows, int cols, int box_rows, int box_cols) {
    cuuint64_t gd[2] = {(cuuint64_t)cols, (cuuint64_t)rows};
    cuuint64_t gs[1] = {(cuuint64_t)cols * 2};
    cuuint32_t bx[2] = {(cuuint32_t)box_cols, (cuuint32_t)box_rows};
    cuuint32_t es[2] = {1, 1};
    enc(m, CU_TENSOR_MAP_DATA_TYPE_BFLOAT16, 2, const_cast<void*>(ptr), gd, gs, bx, es, CU_TENSOR_MAP_INTERLEAVE_NONE,
        CU_TENSOR_MAP_SWIZZLE_128B, CU_TENSOR_MAP_L2_PROMOTION_L2_128B, CU_TENSOR_MAP_FLOAT_OOB_FILL_NONE);
}

}

extern "C" void kernel_launch(void* const* d_in, const int* in_sizes, int n_in, void* d_out, int out_size) {
    const __nv_bfloat16* x = (const __nv_bfloat16*)d_in[0];
    const __nv_bfloat16* sre = (const __nv_bfloat16*)d_in[1];
    const __nv_bfloat16* sim = (const __nv_bfloat16*)d_in[2];
    const __nv_bfloat16* hre = (const __nv_bfloat16*)d_in[3];
    const __nv_bfloat16* him = (const __nv_bfloat16*)d_in[4];
    const __nv_bfloat16* wgt = (const __nv_bfloat16*)d_in[6];
    const __nv_bfloat16* wup = (const __nv_bfloat16*)d_in[7];
    const __nv_bfloat16* wdn = (const __nv_bfloat16*)d_in[8];
    __nv_bfloat16* out = (__nv_bfloat16*)d_out;

    void* fn = nullptr;
    cudaDriverEntryPointQueryResult qr;
    cudaGetDriverEntryPoint("cuTensorMapEncodeTiled", &fn, cudaEnableDefault, &qr);
    EncFn enc = (EncFn)fn;
    void *p_abT, *p_h;
    cudaGetSymbolAddress(&p_abT, g_abT);
    cudaGetSymbolAddress(&p_h, g_h);

    CUtensorMap tm_wg, tm_wu, tm_hre, tm_him, tm_h, tm_abT_st, tm_abT, tm_sre, tm_sim, tm_wd;
    make_map(enc, &tm_wg, wgt, D_, F_, 64, 64);
    make_map(enc, &tm_wu, wup, D_, F_, 64, 64);
    make_map(enc, &tm_hre, hre, D_, D_, 64, 64);
    make_map(enc, &tm_him, him, D_, D_, 64, 64);
    make_map(enc, &tm_h, p_h, S_, F_, 128, 64);
    make_map(enc, &tm_abT_st, p_abT, 896, S_, 64, 64);
    make_map(enc, &tm_abT, p_abT, 896, S_, 112, 64);
    make_map(enc, &tm_sre, sre, S_, S_, 128, 64);
    make_map(enc, &tm_sim, sim, S_, S_, 128, 64);
    make_map(enc, &tm_wd, wdn, F_, D_, 64, 64);

    cudaFuncSetAttribute(kernel_a, cudaFuncAttributeMaxDynamicSharedMemorySize, KA_SMEM);
    cudaFuncSetAttribute(kernel_b, cudaFuncAttributeMaxDynamicSharedMemorySize, KB_SMEM);

    cudaLaunchAttribute at[2];
    at[0].id = cudaLaunchAttributeClusterDimension;
    at[0].val.clusterDim.x = 2; at[0].val.clusterDim.y = 1; at[0].val.clusterDim.z = 1;
    at[1].id = cudaLaunchAttributeProgrammaticStreamSerialization;
    at[1].val.programmaticStreamSerializationAllowed = 1;

    cudaLaunchConfig_t cfg = {};
    cfg.gridDim = dim3(128); cfg.blockDim = dim3(288); cfg.stream = cudaStreamPerThread;
    cfg.attrs = at;
    cfg.dynamicSmemBytes = KA_SMEM; cfg.numAttrs = 1;
    cudaLaunchKernelEx(&cfg, kernel_a, x, tm_wg, tm_wu, tm_hre, tm_him, tm_h, tm_abT_st, sre, sim);
    cfg.dynamicSmemBytes = KB_SMEM; cfg.numAttrs = 2;
    cudaLaunchKernelEx(&cfg, kernel_b, x, out, tm_sre, tm_sim, tm_h, tm_abT, tm_wd);
}
```

```cpp
#include <cuda_runtime.h>
#include <cuda_bf16.h>
#include <cuda.h>
#include <stdint.h>

namespace {

constexpr int S_ = 2048, D_ = 448, F_ = 1792;

__device__ __align__(1024) __nv_bfloat16 g_abT[896 * 2048];
__device__ __align__(1024) __nv_bfloat16 g_h[2048 * 1792];
__device__ __align__(1024) __nv_bfloat16 g_y[2 * 2048 * 448];
struct Flags {
    unsigned int ab[16];
    unsigned int h[16 * 28];
    unsigned int y[32];
    unsigned int done;
};
__device__ Flags g_fl;

#define TL(k, i) do {} while (0)
__device__ __forceinline__ uint32_t s2u(const void* p) { return (uint32_t)__cvta_generic_to_shared(p); }
__device__ __forceinline__ void mbar_init(uint32_t b, int c) {
    asm volatile("mbarrier.init.shared::cta.b64 [%0], %1;" ::"r"(b), "r"(c));
}
__device__ __forceinline__ void mbar_expect(uint32_t b, uint32_t bytes) {
    asm volatile("mbarrier.arrive.expect_tx.shared::cta.b64 _, [%0], %1;" ::"r"(b), "r"(bytes) : "memory");
}
__device__ __forceinline__ void mbar_wait(uint32_t b, uint32_t ph) {
    uint32_t ok;
    do {
        asm volatile("{\n.reg .pred p;\nmbarrier.try_wait.parity.shared::cta.b64 p, [%1], %2;\nselp.u32 %0, 1, 0, p;\n}"
                     : "=r"(ok) : "r"(b), "r"(ph) : "memory");
    } while (!ok);
}
__device__ __forceinline__ void mbar_arrive_both(uint32_t b) {
    asm volatile("{\n.reg .b32 r0, r1;\n"
                 "mapa.shared::cluster.u32 r0, %0, 0;\n"
                 "mapa.shared::cluster.u32 r1, %0, 1;\n"
                 "mbarrier.arrive.shared::cluster.b64 _, [r0];\n"
                 "mbarrier.arrive.shared::cluster.b64 _, [r1];\n}"
                 ::"r"(b) : "memory");
}
__device__ __forceinline__ void tma_load(uint32_t dst, const CUtensorMap* m, uint32_t bar, int c0, int c1) {
    asm volatile("cp.async.bulk.tensor.2d.shared::cluster.global.mbarrier::complete_tx::bytes [%0], [%1, {%3, %4}], [%2];"
                 ::"r"(dst), "l"(m), "r"(bar), "r"(c0), "r"(c1) : "memory");
}
__device__ __forceinline__ void tma_load_mc(uint32_t dst, const CUtensorMap* m, uint32_t bar, int c0, int c1) {
    asm volatile("cp.async.bulk.tensor.2d.shared::cluster.global.mbarrier::complete_tx::bytes.multicast::cluster [%0], [%1, {%3, %4}], [%2], %5;"
                 ::"r"(dst), "l"(m), "r"(bar), "r"(c0), "r"(c1), "h"((uint16_t)3) : "memory");
}
__device__ __forceinline__ void tma_store(const CUtensorMap* m, uint32_t src, int c0, int c1) {
    asm volatile("cp.async.bulk.tensor.2d.global.shared::cta.bulk_group [%0, {%2, %3}], [%1];"
                 ::"l"(m), "r"(src), "r"(c0), "r"(c1) : "memory");
}
__device__ __forceinline__ void bulk_commit() { asm volatile("cp.async.bulk.commit_group;" ::: "memory"); }
__device__ __forceinline__ void bulk_wait_read0() { asm volatile("cp.async.bulk.wait_group.read 0;" ::: "memory"); }
__device__ __forceinline__ void bulk_wait0() { asm volatile("cp.async.bulk.wait_group 0;" ::: "memory"); }
__device__ __forceinline__ void fence_async() { asm volatile("fence.proxy.async.shared::cta;" ::: "memory"); }
__device__ __forceinline__ void fence_async_all() { asm volatile("fence.proxy.async;" ::: "memory"); }
__device__ __forceinline__ void cluster_sync() {
    asm volatile("barrier.cluster.arrive.release.aligned;\nbarrier.cluster.wait.acquire.aligned;" ::: "memory");
}
__device__ __forceinline__ void bar_sync(int id, int n) { asm volatile("bar.sync %0, %1;" ::"r"(id), "r"(n) : "memory"); }
__device__ __forceinline__ void wg_arrive() { asm volatile("wgmma.fence.sync.aligned;" ::: "memory"); }
__device__ __forceinline__ void wg_commit() { asm volatile("wgmma.commit_group.sync.aligned;" ::: "memory"); }
template <int N> __device__ __forceinline__ void wg_wait() { asm volatile("wgmma.wait_group.sync.aligned %0;" ::"n"(N) : "memory"); }
__device__ __forceinline__ void stmat4(uint32_t a, uint32_t r0, uint32_t r1, uint32_t r2, uint32_t r3) {
    asm volatile("stmatrix.sync.aligned.m8n8.x4.shared.b16 [%0], {%1, %2, %3, %4};" ::"r"(a), "r"(r0), "r"(r1), "r"(r2), "r"(r3) : "memory");
}
__device__ __forceinline__ void stmat4t(uint32_t a, uint32_t r0, uint32_t r1, uint32_t r2, uint32_t r3) {
    asm volatile("stmatrix.sync.aligned.m8n8.x4.trans.shared.b16 [%0], {%1, %2, %3, %4};" ::"r"(a), "r"(r0), "r"(r1), "r"(r2), "r"(r3) : "memory");
}
__device__ __forceinline__ void ldmat4(uint32_t a, uint32_t (&r)[4]) {
    asm volatile("ldmatrix.sync.aligned.m8n8.x4.shared.b16 {%0, %1, %2, %3}, [%4];"
                 : "=r"(r[0]), "=r"(r[1]), "=r"(r[2]), "=r"(r[3]) : "r"(a) : "memory");
}
__device__ __forceinline__ void flag_signal(unsigned int* f) {
    fence_async_all();
    asm volatile("red.release.gpu.global.add.u32 [%0], 1;" ::"l"(f) : "memory");
}
__device__ __forceinline__ void flag_wait(const unsigned int* f, unsigned int target) {
    unsigned int v;
    int spins = 0;
    while (true) {
        asm volatile("ld.acquire.gpu.global.u32 %0, [%1];" : "=r"(v) : "l"(f) : "memory");
        if (v >= target || ++spins > (1 << 22)) break;
    }
    fence_async_all();
}
__device__ __forceinline__ uint64_t mkdesc(uint32_t addr, uint32_t lbo, uint32_t sbo) {
    return (uint64_t)((addr & 0x3FFFF) >> 4) | ((uint64_t)(lbo >> 4) << 16) | ((uint64_t)(sbo >> 4) << 32) | (1ull << 62);
}
__device__ __forceinline__ uint32_t pack_bf16(float lo, float hi) {
    uint32_t r;
    asm("cvt.rn.bf16x2.f32 %0, %1, %2;" : "=r"(r) : "f"(hi), "f"(lo));
    return r;
}
__device__ __forceinline__ uint32_t hsub2(uint32_t a, uint32_t b) { uint32_t r; asm("sub.rn.bf16x2 %0, %1, %2;" : "=r"(r) : "r"(a), "r"(b)); return r; }
__device__ __forceinline__ uint32_t hadd2(uint32_t a, uint32_t b) { uint32_t r; asm("add.rn.bf16x2 %0, %1, %2;" : "=r"(r) : "r"(a), "r"(b)); return r; }
__device__ __forceinline__ uint32_t hmul2(uint32_t a, uint32_t b) { uint32_t r; asm("mul.rn.bf16x2 %0, %1, %2;" : "=r"(r) : "r"(a), "r"(b)); return r; }
__device__ __forceinline__ uint32_t hfma2(uint32_t a, uint32_t b, uint32_t c) { uint32_t r; asm("fma.rn.bf16x2 %0, %1, %2, %3;" : "=r"(r) : "r"(a), "r"(b), "r"(c)); return r; }
__device__ __forceinline__ float bf_lo(uint32_t u) { return __uint_as_float(u << 16); }
__device__ __forceinline__ float bf_hi(uint32_t u) { return __uint_as_float(u & 0xffff0000u); }
__device__ __forceinline__ float rbf(float v) { return __bfloat162float(__float2bfloat16_rn(v)); }
__device__ __forceinline__ float tanh_fast(float x) { float r; asm("tanh.approx.f32 %0, %1;" : "=f"(r) : "f"(x)); return r; }
__device__ __forceinline__ float gelu_tanh(float x) {
    float u = x * fmaf(x * x, 0.0356774081f, 0.7978845608f);
    float hx = 0.5f * x;
    return fmaf(hx, tanh_fast(u), hx);
}
__device__ __forceinline__ float silu(float f) { return __fdividef(f, 1.0f + __expf(-f)); }

template <int TB>
__device__ __forceinline__ void wgmma_n128(float (&d)[64], uint64_t da, uint64_t db, int scaleD) {
    asm volatile("{\n.reg .pred p;\nsetp.ne.b32 p, %66, 0;\n"
        "wgmma.mma_async.sync.aligned.m64n128k16.f32.bf16.bf16 {%0, %1, %2, %3, %4, %5, %6, %7, %8, %9, %10, %11, %12, %13, %14, %15, %16, %17, %18, %19, %20, %21, %22, %23, %24, %25, %26, %27, %28, %29, %30, %31, %32, %33, %34, %35, %36, %37, %38, %39, %40, %41, %42, %43, %44, %45, %46, %47, %48, %49, %50, %51, %52, %53, %54, %55, %56, %57, %58, %59, %60, %61, %62, %63}, %64, %65, p, 1, 1, 0, %67;\n}\n"
        : "+f"(d[0]), "+f"(d[1]), "+f"(d[2]), "+f"(d[3]), "+f"(d[4]), "+f"(d[5]), "+f"(d[6]), "+f"(d[7]), "+f"(d[8]), "+f"(d[9]), "+f"(d[10]), "+f"(d[11]), "+f"(d[12]), "+f"(d[13]), "+f"(d[14]), "+f"(d[15]), "+f"(d[16]), "+f"(d[17]), "+f"(d[18]), "+f"(d[19]), "+f"(d[20]), "+f"(d[21]), "+f"(d[22]), "+f"(d[23]), "+f"(d[24]), "+f"(d[25]), "+f"(d[26]), "+f"(d[27]), "+f"(d[28]), "+f"(d[29]), "+f"(d[30]), "+f"(d[31]), "+f"(d[32]), "+f"(d[33]), "+f"(d[34]), "+f"(d[35]), "+f"(d[36]), "+f"(d[37]), "+f"(d[38]), "+f"(d[39]), "+f"(d[40]), "+f"(d[41]), "+f"(d[42]), "+f"(d[43]), "+f"(d[44]), "+f"(d[45]), "+f"(d[46]), "+f"(d[47]), "+f"(d[48]), "+f"(d[49]), "+f"(d[50]), "+f"(d[51]), "+f"(d[52]), "+f"(d[53]), "+f"(d[54]), "+f"(d[55]), "+f"(d[56]), "+f"(d[57]), "+f"(d[58]), "+f"(d[59]), "+f"(d[60]), "+f"(d[61]), "+f"(d[62]), "+f"(d[63])
        : "l"(da), "l"(db), "r"(scaleD), "n"(TB));
}
template <int TB>
__device__ __forceinline__ void wgmma_n224(float (&d)[112], uint64_t da, uint64_t db, int scaleD) {
    asm volatile("{\n.reg .pred p;\nsetp.ne.b32 p, %114, 0;\n"
        "wgmma.mma_async.sync.aligned.m64n224k16.f32.bf16.bf16 {%0, %1, %2, %3, %4, %5, %6, %7, %8, %9, %10, %11, %12, %13, %14, %15, %16, %17, %18, %19, %20, %21, %22, %23, %24, %25, %26, %27, %28, %29, %30, %31, %32, %33, %34, %35, %36, %37, %38, %39, %40, %41, %42, %43, %44, %45, %46, %47, %48, %49, %50, %51, %52, %53, %54, %55, %56, %57, %58, %59, %60, %61, %62, %63, %64, %65, %66, %67, %68, %69, %70, %71, %72, %73, %74, %75, %76, %77, %78, %79, %80, %81, %82, %83, %84, %85, %86, %87, %88, %89, %90, %91, %92, %93, %94, %95, %96, %97, %98, %99, %100, %101, %102, %103, %104, %105, %106, %107, %108, %109, %110, %111}, %112, %113, p, 1, 1, 0, %115;\n}\n"
        : "+f"(d[0]), "+f"(d[1]), "+f"(d[2]), "+f"(d[3]), "+f"(d[4]), "+f"(d[5]), "+f"(d[6]), "+f"(d[7]), "+f"(d[8]), "+f"(d[9]), "+f"(d[10]), "+f"(d[11]), "+f"(d[12]), "+f"(d[13]), "+f"(d[14]), "+f"(d[15]), "+f"(d[16]), "+f"(d[17]), "+f"(d[18]), "+f"(d[19]), "+f"(d[20]), "+f"(d[21]), "+f"(d[22]), "+f"(d[23]), "+f"(d[24]), "+f"(d[25]), "+f"(d[26]), "+f"(d[27]), "+f"(d[28]), "+f"(d[29]), "+f"(d[30]), "+f"(d[31]), "+f"(d[32]), "+f"(d[33]), "+f"(d[34]), "+f"(d[35]), "+f"(d[36]), "+f"(d[37]), "+f"(d[38]), "+f"(d[39]), "+f"(d[40]), "+f"(d[41]), "+f"(d[42]), "+f"(d[43]), "+f"(d[44]), "+f"(d[45]), "+f"(d[46]), "+f"(d[47]), "+f"(d[48]), "+f"(d[49]), "+f"(d[50]), "+f"(d[51]), "+f"(d[52]), "+f"(d[53]), "+f"(d[54]), "+f"(d[55]), "+f"(d[56]), "+f"(d[57]), "+f"(d[58]), "+f"(d[59]), "+f"(d[60]), "+f"(d[61]), "+f"(d[62]), "+f"(d[63]), "+f"(d[64]), "+f"(d[65]), "+f"(d[66]), "+f"(d[67]), "+f"(d[68]), "+f"(d[69]), "+f"(d[70]), "+f"(d[71]), "+f"(d[72]), "+f"(d[73]), "+f"(d[74]), "+f"(d[75]), "+f"(d[76]), "+f"(d[77]), "+f"(d[78]), "+f"(d[79]), "+f"(d[80]), "+f"(d[81]), "+f"(d[82]), "+f"(d[83]), "+f"(d[84]), "+f"(d[85]), "+f"(d[86]), "+f"(d[87]), "+f"(d[88]), "+f"(d[89]), "+f"(d[90]), "+f"(d[91]), "+f"(d[92]), "+f"(d[93]), "+f"(d[94]), "+f"(d[95]), "+f"(d[96]), "+f"(d[97]), "+f"(d[98]), "+f"(d[99]), "+f"(d[100]), "+f"(d[101]), "+f"(d[102]), "+f"(d[103]), "+f"(d[104]), "+f"(d[105]), "+f"(d[106]), "+f"(d[107]), "+f"(d[108]), "+f"(d[109]), "+f"(d[110]), "+f"(d[111])
        : "l"(da), "l"(db), "r"(scaleD), "n"(TB));
}

constexpr int S1_STAGES = 5;
constexpr int S1_XN = 0;
constexpr int S1_B = 7 * 16384;
constexpr int STG = S1_B + S1_STAGES * 16384;
constexpr int S2_STAGES = 4;
constexpr int S2_STAGE = 49152;
constexpr int BAR = STG + 2 * 16384;
constexpr int BAR_F1 = BAR, BAR_E1 = BAR + 40, BAR_F2 = BAR + 80, BAR_E2 = BAR + 112, BAR_S1DONE = BAR + 144, BAR_Y = BAR + 152;
constexpr int SMEM_BYTES = BAR + 256 + 1024;
constexpr int TBOX = 128 * 112;

__device__ __forceinline__ int n_passes(int j) { return j < 4 ? 2 : (j < 6 ? 3 : (j == 6 ? 11 : 10)); }
__device__ __forceinline__ int pass_slab(int j, int p) {
    if (p == 0) return j < 7 ? -1 : 0;
    if (p == 1) return 1 + j;
    if (p == 2) return 5 + j;
    return 13 + 2 * (p - 3) + (j - 6);
}

template <int TB>
__device__ __forceinline__ void s1_mainloop(float (&acc)[2][64], uint32_t sb, int idx, int lane, int handoff) {
    int st = idx % S1_STAGES;
    uint32_t ph = (idx / S1_STAGES) & 1;
    int prev = 0;
    uint64_t da = mkdesc(sb + S1_XN, 16, 1024);
    const uint64_t db0 = TB ? mkdesc(sb + S1_B, 8192, 1024) : mkdesc(sb + S1_B, 16, 1024);
#pragma unroll 1
    for (int kb = 0; kb < 7; kb++) {
        mbar_wait(sb + BAR_F1 + 8 * st, ph);
        if (kb == 6 && handoff) asm volatile("bar.arrive %0, 256;" ::"r"(handoff) : "memory");
        const uint64_t db = db0 + st * 1024;
        wg_arrive();
#pragma unroll
        for (int s = 0; s < 4; s++) {
            wgmma_n128<TB>(acc[0], da + s * 2, db + s * (TB ? 128 : 2), kb | s);
            wgmma_n128<TB>(acc[1], da + 512 + s * 2, db + s * (TB ? 128 : 2), kb | s);
        }
        wg_commit();
        wg_wait<1>();
        if (kb > 0 && lane == 0) mbar_arrive_both(sb + BAR_E1 + 8 * prev);
        prev = st;
        da += 1024;
        if (++st == S1_STAGES) { st = 0; ph ^= 1; }
    }
    wg_wait<0>();
    if (lane == 0) mbar_arrive_both(sb + BAR_E1 + 8 * prev);
}

template <int TB>
__device__ __forceinline__ void s2_mainloop(float (&acc)[112], uint32_t sb, int nkb, int wg, int lane) {
    int st = 0;
    uint32_t ph = 0;
    int prev = 0;
    const uint64_t da0 = mkdesc(sb + wg * 8192, 16, 1024);
    const uint64_t db0 = TB ? mkdesc(sb + 16384, 8192, 1024) : mkdesc(sb + 16384, 16, 1024);
#pragma unroll 1
    for (int i = 0; i < nkb; i++) {
        mbar_wait(sb + BAR_F2 + 8 * st, ph);
        const uint64_t da = da0 + st * (S2_STAGE / 16), db = db0 + st * (S2_STAGE / 16);
        wg_arrive();
#pragma unroll
        for (int s = 0; s < 4; s++) wgmma_n224<TB>(acc, da + s * 2, db + s * (TB ? 128 : 2), i | s);
        wg_commit();
        wg_wait<1>();
        if (i > 0 && lane == 0) mbar_arrive_both(sb + BAR_E2 + 8 * prev);
        prev = st;
        if (++st == S2_STAGES) { st = 0; ph ^= 1; }
    }
    wg_wait<0>();
    if (lane == 0) mbar_arrive_both(sb + BAR_E2 + 8 * prev);
}

struct Maps {
    CUtensorMap wg, wu, hre, him, h, abT_st, abT, sre, sim, wd, x, y, out;
};

__global__ void __launch_bounds__(288, 1)
fused_kernel(const __nv_bfloat16* __restrict__ x, const __grid_constant__ Maps tm) {
    extern __shared__ unsigned char smem_raw[];
    const uint32_t sb = (s2u(smem_raw) + 1023) & ~1023u;
    const int tid = threadIdx.x, lane = tid & 31;
    const int warp = __shfl_sync(0xffffffffu, tid >> 5, 0);
    const int rank = blockIdx.x & 1;
    const int cid = blockIdx.x >> 1;
    const int j = cid & 7;
    const int rb = (cid >> 3) * 2 + rank;
    const int npass = n_passes(j);
    const int n = j & 1;
    const int part = j >> 1;

    if (tid == 0) {
        TL(0, 0);
        for (int i = 0; i < S1_STAGES; i++) { mbar_init(sb + BAR_F1 + 8 * i, 1); mbar_init(sb + BAR_E1 + 8 * i, 8); }
        for (int i = 0; i < S2_STAGES; i++) { mbar_init(sb + BAR_F2 + 8 * i, 1); mbar_init(sb + BAR_E2 + 8 * i, 16); }
        mbar_init(sb + BAR_S1DONE, 16);
        mbar_init(sb + BAR_Y, 1);
        asm volatile("fence.mbarrier_init.release.cluster;" ::: "memory");
    }
    cluster_sync();

    if (warp == 8) {
        if (lane == 0) {
            int st = 0;
            uint32_t ph = 1;
            for (int p = 0; p < npass; p++) {
                const int slab = pass_slab(j, p);
                for (int kb = 0; kb < 7; kb++) {
                    mbar_wait(sb + BAR_E1 + 8 * st, ph);
                    const uint32_t dst = sb + S1_B + st * 16384 + rank * 8192;
                    const uint32_t fb = sb + BAR_F1 + 8 * st;
                    mbar_expect(fb, 16384);
                    if (slab >= 0) {
                        tma_load_mc(dst, rank ? &tm.wu : &tm.wg, fb, slab * 64, kb * 64);
                    } else {
                        const int a = 2 * j + rank;
                        tma_load_mc(dst, a < 7 ? &tm.hre : &tm.him, fb, kb * 64, (a < 7 ? a : a - 7) * 64);
                    }
                    if (++st == S1_STAGES) { st = 0; ph ^= 1; }
                }
            }
            if (part < 3) {
                mbar_wait(sb + BAR_S1DONE, 0);
                TL(0, 24);
                st = 0; ph = 1;
                if (part < 2) {
                    const CUtensorMap* ma = part ? &tm.sim : &tm.sre;
                    for (int g = 0; g < 32; g++) {
                        mbar_wait(sb + BAR_E2 + 8 * st, ph);
                        const uint32_t dst = sb + st * S2_STAGE;
                        const uint32_t fb = sb + BAR_F2 + 8 * st;
                        mbar_expect(fb, 16384 + 28672);
                        tma_load(dst, ma, fb, g * 64, rb * 128);
                        if ((g & 1) == 0) flag_wait(&g_fl.ab[g >> 1], 7);
                        tma_load_mc(dst + 16384 + rank * 14336, &tm.abT, fb, g * 64, part * 448 + n * 224 + rank * 112);
                        if (++st == S2_STAGES) { st = 0; ph ^= 1; }
                    }
                } else {
                    for (int g = 0; g < 28; g++) {
                        mbar_wait(sb + BAR_E2 + 8 * st, ph);
                        const uint32_t dst = sb + st * S2_STAGE;
                        const uint32_t fb = sb + BAR_F2 + 8 * st;
                        mbar_expect(fb, 16384 + 32768);
                        tma_load_mc(dst + 16384 + (2 * rank) * 8192, &tm.wd, fb, n * 224 + (2 * rank) * 64, g * 64);
                        tma_load_mc(dst + 16384 + (2 * rank + 1) * 8192, &tm.wd, fb, n * 224 + (2 * rank + 1) * 64, g * 64);
                        flag_wait(&g_fl.h[rb * 28 + g], 1);
                        tma_load(dst, &tm.h, fb, g * 64, rb * 128);
                        if (++st == S2_STAGES) { st = 0; ph ^= 1; }
                    }
                    for (int i = 0; i < S2_STAGES; i++) {
                        mbar_wait(sb + BAR_E2 + 8 * st, ph);
                        if (++st == S2_STAGES) { st = 0; ph ^= 1; }
                    }
                    mbar_expect(sb + BAR_Y, 12 * TBOX);
                    for (int q = 0; q < 4; q++) tma_load(sb + q * TBOX, &tm.x, sb + BAR_Y, n * 224 + q * 56, rb * 128);
                    flag_wait(&g_fl.y[rb * 2 + n], 2);
                    for (int q = 0; q < 8; q++)
                        tma_load(sb + (4 + q) * TBOX, &tm.y, sb + BAR_Y, n * 224 + (q & 3) * 56, (q >> 2) * S_ + rb * 128);
                }
            }
        }
        __syncwarp();
    } else {
        {
            const int l8 = lane & 7, sub = lane >> 3;
            uint4 v[4][7];
#pragma unroll
            for (int it = 0; it < 4; it++) {
                const uint4* src = reinterpret_cast<const uint4*>(x + (size_t)(rb * 128 + warp * 16 + it * 4 + sub) * D_) + l8;
#pragma unroll
                for (int i = 0; i < 7; i++) v[it][i] = __ldg(src + i * 8);
            }
#pragma unroll
            for (int it = 0; it < 4; it++) {
                const int row = warp * 16 + it * 4 + sub;
                float s0 = 0.f, s1 = 0.f;
#pragma unroll
                for (int i = 0; i < 7; i++) {
                    s0 += (bf_lo(v[it][i].x) + bf_hi(v[it][i].x)) + (bf_lo(v[it][i].y) + bf_hi(v[it][i].y));
                    s1 += (bf_lo(v[it][i].z) + bf_hi(v[it][i].z)) + (bf_lo(v[it][i].w) + bf_hi(v[it][i].w));
                }
                float s = s0 + s1;
                s += __shfl_xor_sync(0xffffffffu, s, 1);
                s += __shfl_xor_sync(0xffffffffu, s, 2);
                s += __shfl_xor_sync(0xffffffffu, s, 4);
                const float mean = s * (1.0f / D_);
                float q0 = 0.f, q1 = 0.f;
#pragma unroll
                for (int i = 0; i < 7; i++) {
                    const uint32_t w[4] = {v[it][i].x, v[it][i].y, v[it][i].z, v[it][i].w};
#pragma unroll
                    for (int c = 0; c < 4; c++) {
                        const float d0 = bf_lo(w[c]) - mean, d1 = bf_hi(w[c]) - mean;
                        q0 = fmaf(d0, d0, q0);
                        q1 = fmaf(d1, d1, q1);
                    }
                }
                float q = q0 + q1;
                q += __shfl_xor_sync(0xffffffffu, q, 1);
                q += __shfl_xor_sync(0xffffffffu, q, 2);
                q += __shfl_xor_sync(0xffffffffu, q, 4);
                const float var = rbf(q * (1.0f / D_));
                const float den = rbf(sqrtf(rbf(var + 1e-5f)));
                const float rinv = 1.0f / den;
                const float rhi = rbf(rinv);
                const uint32_t m2 = pack_bf16(mean, mean), rhi2 = pack_bf16(rhi, rhi), rlo2 = pack_bf16(rinv - rhi, rinv - rhi);
                const uint32_t dst = sb + S1_XN + row * 128 + ((l8 ^ (row & 7)) << 4);
#pragma unroll
                for (int i = 0; i < 7; i++) {
                    const uint32_t w[4] = {v[it][i].x, v[it][i].y, v[it][i].z, v[it][i].w};
                    uint32_t o[4];
#pragma unroll
                    for (int c = 0; c < 4; c++) {
                        const uint32_t xc = hsub2(w[c], m2);
                        o[c] = hfma2(xc, rhi2, hmul2(xc, rlo2));
                    }
                    asm volatile("st.shared.v4.b32 [%0], {%1, %2, %3, %4};" ::"r"(dst + i * 16384), "r"(o[0]), "r"(o[1]), "r"(o[2]), "r"(o[3]) : "memory");
                }
            }
            fence_async();
            bar_sync(1, 256);
            if (tid == 0) TL(0, 2);
        }
        const int wg = warp >> 2, wl = warp & 3, wtid = tid & 127;
        const uint32_t stg = sb + STG + wg * 16384;
        {
            float acc[2][64];
            for (int p = wg; p < npass; p += 2) {
                const int slab = pass_slab(j, p);
                if (p > 0) bar_sync(4 + (p & 1), 256);
                const int handoff = (p + 1 < npass) ? 4 + ((p + 1) & 1) : 0;
                if (slab >= 0) s1_mainloop<1>(acc, sb, p * 7, lane, handoff);
                else s1_mainloop<0>(acc, sb, p * 7, lane, handoff);
                if (p + 2 >= npass && lane == 0) mbar_arrive_both(sb + BAR_S1DONE);
                if (wtid == 0 && p < 4) TL(0, 4 + p);

                if (slab >= 0) {
                    bar_sync(2 + wg, 128);
#pragma unroll
                    for (int mh = 0; mh < 2; mh++) {
                        const int row = mh * 64 + wl * 16 + (lane & 7) + ((lane >> 3) & 1) * 8;
#pragma unroll
                        for (int jj = 0; jj < 8; jj += 2) {
                            uint32_t r[4];
#pragma unroll
                            for (int t = 0; t < 4; t++) {
                                const int o = (jj + (t >> 1)) * 4 + (t & 1) * 2;
                                const uint32_t g2 = pack_bf16(acc[mh][o], acc[mh][o + 1]);
                                const uint32_t u2 = pack_bf16(acc[mh][32 + o], acc[mh][32 + o + 1]);
                                const uint32_t a2 = pack_bf16(gelu_tanh(bf_lo(g2)), gelu_tanh(bf_hi(g2)));
                                r[t] = hmul2(a2, u2);
                            }
                            const int chunk = jj + (lane >> 4);
                            stmat4(stg + row * 128 + ((chunk ^ (row & 7)) << 4), r[0], r[1], r[2], r[3]);
                        }
                    }
                    fence_async();
                    bar_sync(2 + wg, 128);
                    if (wtid == 0) {
                        tma_store(&tm.h, stg, slab * 64, rb * 128);
                        bulk_commit();
                        bulk_wait0();
                        flag_signal(&g_fl.h[rb * 28 + slab]);
                    }
                } else {
#pragma unroll
                    for (int hf = 0; hf < 2; hf++) {
                        if (hf == 1 && wtid == 0) bulk_wait_read0();
                        bar_sync(2 + wg, 128);
#pragma unroll
                        for (int mh = 0; mh < 2; mh++) {
#pragma unroll
                            for (int jj = 0; jj < 8; jj += 2) {
                                uint32_t r[4];
#pragma unroll
                                for (int t = 0; t < 4; t++) {
                                    const int o = hf * 32 + (jj + (t >> 1)) * 4 + (t & 1) * 2;
                                    r[t] = pack_bf16(acc[mh][o], acc[mh][o + 1]);
                                }
                                const int e = 8 * (jj + (lane >> 4)) + (lane & 7);
                                const int sc = 2 * wl + ((lane >> 3) & 1);
                                stmat4t(stg + mh * 8192 + e * 128 + ((sc ^ (e & 7)) << 4), r[0], r[1], r[2], r[3]);
                            }
                        }
                        fence_async();
                        bar_sync(2 + wg, 128);
                        if (wtid == 0) {
                            tma_store(&tm.abT_st, stg, rb * 128, (2 * j + hf) * 64);
                            tma_store(&tm.abT_st, stg + 8192, rb * 128 + 64, (2 * j + hf) * 64);
                            bulk_commit();
                        }
                    }
                    if (wtid == 0) {
                        bulk_wait0();
                        flag_signal(&g_fl.ab[rb]);
                    }
                }
                if (wtid == 0 && p < 4) TL(0, 10 + p);
            }
        }
        if (wtid == 0) TL(0, 20 + wg);
        if (part < 3) {
            float acc[112];
            if (part < 2) s2_mainloop<0>(acc, sb, 32, wg, lane);
            else s2_mainloop<1>(acc, sb, 28, wg, lane);
            if (tid == 0) TL(0, 25);
            const int frow = wg * 64 + wl * 16 + (lane & 7) + ((lane >> 3) & 1) * 8;
            if (part < 2) {
                bar_sync(1, 256);
#pragma unroll
                for (int q = 0; q < 14; q++) {
                    const int nb = 2 * q + (lane >> 4);
                    const uint32_t a = sb + (nb / 7) * TBOX + frow * 112 + (nb % 7) * 16;
                    stmat4(a, pack_bf16(acc[8 * q], acc[8 * q + 1]), pack_bf16(acc[8 * q + 2], acc[8 * q + 3]),
                           pack_bf16(acc[8 * q + 4], acc[8 * q + 5]), pack_bf16(acc[8 * q + 6], acc[8 * q + 7]));
                }
                fence_async();
                bar_sync(1, 256);
                if (tid == 0) {
                    for (int q = 0; q < 4; q++) tma_store(&tm.y, sb + q * TBOX, n * 224 + q * 56, part * S_ + rb * 128);
                    bulk_commit();
                    bulk_wait0();
                    flag_signal(&g_fl.y[rb * 2 + n]);
                }
            } else {
                mbar_wait(sb + BAR_Y, 0);
                if (tid == 0) TL(0, 26);
#pragma unroll
                for (int q = 0; q < 14; q++) {
                    const int nb = 2 * q + (lane >> 4);
                    const uint32_t a = sb + (nb / 7) * TBOX + frow * 112 + (nb % 7) * 16;
                    uint32_t xv[4], yr[4], yi[4], o[4];
                    ldmat4(a, xv);
                    ldmat4(a + 4 * TBOX, yr);
                    ldmat4(a + 8 * TBOX, yi);
#pragma unroll
                    for (int t = 0; t < 4; t++) {
                        const uint32_t f2 = pack_bf16(acc[8 * q + 2 * t], acc[8 * q + 2 * t + 1]);
                        const uint32_t g2 = pack_bf16(silu(bf_lo(f2)), silu(bf_hi(f2)));
                        o[t] = hadd2(xv[t], hmul2(hsub2(yr[t], yi[t]), g2));
                    }
                    stmat4(a, o[0], o[1], o[2], o[3]);
                }
                fence_async();
                bar_sync(1, 256);
                if (tid == 0) {
                    for (int q = 0; q < 4; q++) tma_store(&tm.out, sb + q * TBOX, n * 224 + q * 56, rb * 128);
                    bulk_commit();
                    bulk_wait0();
                }
            }
        }
    }
    cluster_sync();
    if (tid == 0) {
        TL(0, 30);
        __threadfence();
        if (atomicAdd(&g_fl.done, 1u) == gridDim.x - 1) {
            unsigned int* f = reinterpret_cast<unsigned int*>(&g_fl);
            for (int i = 0; i < (int)(sizeof(Flags) / 4); i++) f[i] = 0;
        }
    }
}

typedef CUresult (*EncFn)(CUtensorMap*, CUtensorMapDataType, cuuint32_t, void*, const cuuint64_t*, const cuuint64_t*,
                          const cuuint32_t*, const cuuint32_t*, CUtensorMapInterleave, CUtensorMapSwizzle,
                          CUtensorMapL2promotion, CUtensorMapFloatOOBfill);

void make_map(EncFn enc, CUtensorMap* m, const void* ptr, int rows, int cols, int box_rows, int box_cols, bool swz = true) {
    cuuint64_t gd[2] = {(cuuint64_t)cols, (cuuint64_t)rows};
    cuuint64_t gs[1] = {(cuuint64_t)cols * 2};
    cuuint32_t bx[2] = {(cuuint32_t)box_cols, (cuuint32_t)box_rows};
    cuuint32_t es[2] = {1, 1};
    enc(m, CU_TENSOR_MAP_DATA_TYPE_BFLOAT16, 2, const_cast<void*>(ptr), gd, gs, bx, es, CU_TENSOR_MAP_INTERLEAVE_NONE,
        swz ? CU_TENSOR_MAP_SWIZZLE_128B : CU_TENSOR_MAP_SWIZZLE_NONE, CU_TENSOR_MAP_L2_PROMOTION_L2_128B,
        CU_TENSOR_MAP_FLOAT_OOB_FILL_NONE);
}

}

extern "C" void kernel_launch(void* const* d_in, const int* in_sizes, int n_in, void* d_out, int out_size) {
    const __nv_bfloat16* x = (const __nv_bfloat16*)d_in[0];

    void* fn = nullptr;
    cudaDriverEntryPointQueryResult qr;
    cudaGetDriverEntryPoint("cuTensorMapEncodeTiled", &fn, cudaEnableDefault, &qr);
    EncFn enc = (EncFn)fn;
    void *p_abT, *p_h, *p_y;
    cudaGetSymbolAddress(&p_abT, g_abT);
    cudaGetSymbolAddress(&p_h, g_h);
    cudaGetSymbolAddress(&p_y, g_y);

    Maps tm;
    make_map(enc, &tm.wg, d_in[6], D_, F_, 64, 64);
    make_map(enc, &tm.wu, d_in[7], D_, F_, 64, 64);
    make_map(enc, &tm.hre, d_in[3], D_, D_, 64, 64);
    make_map(enc, &tm.him, d_in[4], D_, D_, 64, 64);
    make_map(enc, &tm.h, p_h, S_, F_, 128, 64);
    make_map(enc, &tm.abT_st, p_abT, 896, S_, 64, 64);
    make_map(enc, &tm.abT, p_abT, 896, S_, 112, 64);
    make_map(enc, &tm.sre, d_in[1], S_, S_, 128, 64);
    make_map(enc, &tm.sim, d_in[2], S_, S_, 128, 64);
    make_map(enc, &tm.wd, d_in[8], F_, D_, 64, 64);
    make_map(enc, &tm.x, d_in[0], S_, D_, 128, 56, false);
    make_map(enc, &tm.y, p_y, 2 * S_, D_, 128, 56, false);
    make_map(enc, &tm.out, d_out, S_, D_, 128, 56, false);

    cudaFuncSetAttribute(fused_kernel, cudaFuncAttributeMaxDynamicSharedMemorySize, SMEM_BYTES);

    cudaLaunchAttribute at[1];
    at[0].id = cudaLaunchAttributeClusterDimension;
    at[0].val.clusterDim.x = 2; at[0].val.clusterDim.y = 1; at[0].val.clusterDim.z = 1;
    cudaLaunchConfig_t cfg = {};
    cfg.gridDim = dim3(128); cfg.blockDim = dim3(288); cfg.stream = cudaStreamPerThread;
    cfg.attrs = at; cfg.numAttrs = 1;
    cfg.dynamicSmemBytes = SMEM_BYTES;
    cudaLaunchKernelEx(&cfg, fused_kernel, x, tm);
}
```

```cpp
#include <cuda_runtime.h>
#include <cuda_bf16.h>
#include <cuda.h>
#include <stdint.h>

namespace {

constexpr int S_ = 2048, D_ = 448, F_ = 1792;

__device__ __align__(1024) __nv_bfloat16 g_abT[896 * 2048];
__device__ __align__(1024) __nv_bfloat16 g_h[2048 * 1792];
__device__ __align__(1024) __nv_bfloat16 g_y[2 * 2048 * 448];
struct Flags {
    unsigned int ab[16];
    unsigned int h[16 * 28];
    unsigned int y[32];
    unsigned int done;
};
__device__ Flags g_fl;

#define TL(k, i) do {} while (0)
__device__ __forceinline__ uint32_t s2u(const void* p) { return (uint32_t)__cvta_generic_to_shared(p); }
__device__ __forceinline__ void mbar_init(uint32_t b, int c) {
    asm volatile("mbarrier.init.shared::cta.b64 [%0], %1;" ::"r"(b), "r"(c));
}
__device__ __forceinline__ void mbar_expect(uint32_t b, uint32_t bytes) {
    asm volatile("mbarrier.arrive.expect_tx.shared::cta.b64 _, [%0], %1;" ::"r"(b), "r"(bytes) : "memory");
}
__device__ __forceinline__ void mbar_wait(uint32_t b, uint32_t ph) {
    uint32_t ok;
    do {
        asm volatile("{\n.reg .pred p;\nmbarrier.try_wait.parity.shared::cta.b64 p, [%1], %2;\nselp.u32 %0, 1, 0, p;\n}"
                     : "=r"(ok) : "r"(b), "r"(ph) : "memory");
    } while (!ok);
}
__device__ __forceinline__ void mbar_arrive_both(uint32_t b) {
    asm volatile("{\n.reg .b32 r0, r1;\n"
                 "mapa.shared::cluster.u32 r0, %0, 0;\n"
                 "mapa.shared::cluster.u32 r1, %0, 1;\n"
                 "mbarrier.arrive.shared::cluster.b64 _, [r0];\n"
                 "mbarrier.arrive.shared::cluster.b64 _, [r1];\n}"
                 ::"r"(b) : "memory");
}
__device__ __forceinline__ void tma_load(uint32_t dst, const CUtensorMap* m, uint32_t bar, int c0, int c1) {
    asm volatile("cp.async.bulk.tensor.2d.shared::cluster.global.mbarrier::complete_tx::bytes [%0], [%1, {%3, %4}], [%2];"
                 ::"r"(dst), "l"(m), "r"(bar), "r"(c0), "r"(c1) : "memory");
}
__device__ __forceinline__ void tma_load_mc(uint32_t dst, const CUtensorMap* m, uint32_t bar, int c0, int c1) {
    asm volatile("cp.async.bulk.tensor.2d.shared::cluster.global.mbarrier::complete_tx::bytes.multicast::cluster [%0], [%1, {%3, %4}], [%2], %5;"
                 ::"r"(dst), "l"(m), "r"(bar), "r"(c0), "r"(c1), "h"((uint16_t)3) : "memory");
}
__device__ __forceinline__ void tma_store(const CUtensorMap* m, uint32_t src, int c0, int c1) {
    asm volatile("cp.async.bulk.tensor.2d.global.shared::cta.bulk_group [%0, {%2, %3}], [%1];"
                 ::"l"(m), "r"(src), "r"(c0), "r"(c1) : "memory");
}
__device__ __forceinline__ void bulk_commit() { asm volatile("cp.async.bulk.commit_group;" ::: "memory"); }
__device__ __forceinline__ void bulk_wait_read0() { asm volatile("cp.async.bulk.wait_group.read 0;" ::: "memory"); }
__device__ __forceinline__ void bulk_wait0() { asm volatile("cp.async.bulk.wait_group 0;" ::: "memory"); }
__device__ __forceinline__ void fence_async() { asm volatile("fence.proxy.async.shared::cta;" ::: "memory"); }
__device__ __forceinline__ void fence_async_all() { asm volatile("fence.proxy.async;" ::: "memory"); }
__device__ __forceinline__ void cluster_sync() {
    asm volatile("barrier.cluster.arrive.release.aligned;\nbarrier.cluster.wait.acquire.aligned;" ::: "memory");
}
__device__ __forceinline__ void bar_sync(int id, int n) { asm volatile("bar.sync %0, %1;" ::"r"(id), "r"(n) : "memory"); }
__device__ __forceinline__ void wg_arrive() { asm volatile("wgmma.fence.sync.aligned;" ::: "memory"); }
__device__ __forceinline__ void wg_commit() { asm volatile("wgmma.commit_group.sync.aligned;" ::: "memory"); }
template <int N> __device__ __forceinline__ void wg_wait() { asm volatile("wgmma.wait_group.sync.aligned %0;" ::"n"(N) : "memory"); }
__device__ __forceinline__ void stmat4(uint32_t a, uint32_t r0, uint32_t r1, uint32_t r2, uint32_t r3) {
    asm volatile("stmatrix.sync.aligned.m8n8.x4.shared.b16 [%0], {%1, %2, %3, %4};" ::"r"(a), "r"(r0), "r"(r1), "r"(r2), "r"(r3) : "memory");
}
__device__ __forceinline__ void stmat4t(uint32_t a, uint32_t r0, uint32_t r1, uint32_t r2, uint32_t r3) {
    asm volatile("stmatrix.sync.aligned.m8n8.x4.trans.shared.b16 [%0], {%1, %2, %3, %4};" ::"r"(a), "r"(r0), "r"(r1), "r"(r2), "r"(r3) : "memory");
}
__device__ __forceinline__ void ldmat4(uint32_t a, uint32_t (&r)[4]) {
    asm volatile("ldmatrix.sync.aligned.m8n8.x4.shared.b16 {%0, %1, %2, %3}, [%4];"
                 : "=r"(r[0]), "=r"(r[1]), "=r"(r[2]), "=r"(r[3]) : "r"(a) : "memory");
}
__device__ __forceinline__ void flag_signal(unsigned int* f) {
    fence_async_all();
    asm volatile("red.release.gpu.global.add.u32 [%0], 1;" ::"l"(f) : "memory");
}
__device__ __forceinline__ void flag_wait(const unsigned int* f, unsigned int target) {
    unsigned int v;
    int spins = 0;
    while (true) {
        asm volatile("ld.acquire.gpu.global.u32 %0, [%1];" : "=r"(v) : "l"(f) : "memory");
        if (v >= target || ++spins > (1 << 22)) break;
    }
    fence_async_all();
}
__device__ __forceinline__ uint64_t mkdesc(uint32_t addr, uint32_t lbo, uint32_t sbo) {
    return (uint64_t)((addr & 0x3FFFF) >> 4) | ((uint64_t)(lbo >> 4) << 16) | ((uint64_t)(sbo >> 4) << 32) | (1ull << 62);
}
__device__ __forceinline__ uint32_t pack_bf16(float lo, float hi) {
    uint32_t r;
    asm("cvt.rn.bf16x2.f32 %0, %1, %2;" : "=r"(r) : "f"(hi), "f"(lo));
    return r;
}
__device__ __forceinline__ uint32_t hsub2(uint32_t a, uint32_t b) { uint32_t r; asm("sub.rn.bf16x2 %0, %1, %2;" : "=r"(r) : "r"(a), "r"(b)); return r; }
__device__ __forceinline__ uint32_t hadd2(uint32_t a, uint32_t b) { uint32_t r; asm("add.rn.bf16x2 %0, %1, %2;" : "=r"(r) : "r"(a), "r"(b)); return r; }
__device__ __forceinline__ uint32_t hmul2(uint32_t a, uint32_t b) { uint32_t r; asm("mul.rn.bf16x2 %0, %1, %2;" : "=r"(r) : "r"(a), "r"(b)); return r; }
__device__ __forceinline__ uint32_t hfma2(uint32_t a, uint32_t b, uint32_t c) { uint32_t r; asm("fma.rn.bf16x2 %0, %1, %2, %3;" : "=r"(r) : "r"(a), "r"(b), "r"(c)); return r; }
__device__ __forceinline__ float bf_lo(uint32_t u) { return __uint_as_float(u << 16); }
__device__ __forceinline__ float bf_hi(uint32_t u) { return __uint_as_float(u & 0xffff0000u); }
__device__ __forceinline__ float rbf(float v) { return __bfloat162float(__float2bfloat16_rn(v)); }
__device__ __forceinline__ float tanh_fast(float x) { float r; asm("tanh.approx.f32 %0, %1;" : "=f"(r) : "f"(x)); return r; }
__device__ __forceinline__ float gelu_tanh(float x) {
    float u = x * fmaf(x * x, 0.0356774081f, 0.7978845608f);
    float hx = 0.5f * x;
    return fmaf(hx, tanh_fast(u), hx);
}
__device__ __forceinline__ float silu(float f) { return __fdividef(f, 1.0f + __expf(-f)); }

template <int TB>
__device__ __forceinline__ void wgmma_n128(float (&d)[64], uint64_t da, uint64_t db, int scaleD) {
    asm volatile("{\n.reg .pred p;\nsetp.ne.b32 p, %66, 0;\n"
        "wgmma.mma_async.sync.aligned.m64n128k16.f32.bf16.bf16 {%0, %1, %2, %3, %4, %5, %6, %7, %8, %9, %10, %11, %12, %13, %14, %15, %16, %17, %18, %19, %20, %21, %22, %23, %24, %25, %26, %27, %28, %29, %30, %31, %32, %33, %34, %35, %36, %37, %38, %39, %40, %41, %42, %43, %44, %45, %46, %47, %48, %49, %50, %51, %52, %53, %54, %55, %56, %57, %58, %59, %60, %61, %62, %63}, %64, %65, p, 1, 1, 0, %67;\n}\n"
        : "+f"(d[0]), "+f"(d[1]), "+f"(d[2]), "+f"(d[3]), "+f"(d[4]), "+f"(d[5]), "+f"(d[6]), "+f"(d[7]), "+f"(d[8]), "+f"(d[9]), "+f"(d[10]), "+f"(d[11]), "+f"(d[12]), "+f"(d[13]), "+f"(d[14]), "+f"(d[15]), "+f"(d[16]), "+f"(d[17]), "+f"(d[18]), "+f"(d[19]), "+f"(d[20]), "+f"(d[21]), "+f"(d[22]), "+f"(d[23]), "+f"(d[24]), "+f"(d[25]), "+f"(d[26]), "+f"(d[27]), "+f"(d[28]), "+f"(d[29]), "+f"(d[30]), "+f"(d[31]), "+f"(d[32]), "+f"(d[33]), "+f"(d[34]), "+f"(d[35]), "+f"(d[36]), "+f"(d[37]), "+f"(d[38]), "+f"(d[39]), "+f"(d[40]), "+f"(d[41]), "+f"(d[42]), "+f"(d[43]), "+f"(d[44]), "+f"(d[45]), "+f"(d[46]), "+f"(d[47]), "+f"(d[48]), "+f"(d[49]), "+f"(d[50]), "+f"(d[51]), "+f"(d[52]), "+f"(d[53]), "+f"(d[54]), "+f"(d[55]), "+f"(d[56]), "+f"(d[57]), "+f"(d[58]), "+f"(d[59]), "+f"(d[60]), "+f"(d[61]), "+f"(d[62]), "+f"(d[63])
        : "l"(da), "l"(db), "r"(scaleD), "n"(TB));
}
template <int TB>
__device__ __forceinline__ void wgmma_n224(float (&d)[112], uint64_t da, uint64_t db, int scaleD) {
    asm volatile("{\n.reg .pred p;\nsetp.ne.b32 p, %114, 0;\n"
        "wgmma.mma_async.sync.aligned.m64n224k16.f32.bf16.bf16 {%0, %1, %2, %3, %4, %5, %6, %7, %8, %9, %10, %11, %12, %13, %14, %15, %16, %17, %18, %19, %20, %21, %22, %23, %24, %25, %26, %27, %28, %29, %30, %31, %32, %33, %34, %35, %36, %37, %38, %39, %40, %41, %42, %43, %44, %45, %46, %47, %48, %49, %50, %51, %52, %53, %54, %55, %56, %57, %58, %59, %60, %61, %62, %63, %64, %65, %66, %67, %68, %69, %70, %71, %72, %73, %74, %75, %76, %77, %78, %79, %80, %81, %82, %83, %84, %85, %86, %87, %88, %89, %90, %91, %92, %93, %94, %95, %96, %97, %98, %99, %100, %101, %102, %103, %104, %105, %106, %107, %108, %109, %110, %111}, %112, %113, p, 1, 1, 0, %115;\n}\n"
        : "+f"(d[0]), "+f"(d[1]), "+f"(d[2]), "+f"(d[3]), "+f"(d[4]), "+f"(d[5]), "+f"(d[6]), "+f"(d[7]), "+f"(d[8]), "+f"(d[9]), "+f"(d[10]), "+f"(d[11]), "+f"(d[12]), "+f"(d[13]), "+f"(d[14]), "+f"(d[15]), "+f"(d[16]), "+f"(d[17]), "+f"(d[18]), "+f"(d[19]), "+f"(d[20]), "+f"(d[21]), "+f"(d[22]), "+f"(d[23]), "+f"(d[24]), "+f"(d[25]), "+f"(d[26]), "+f"(d[27]), "+f"(d[28]), "+f"(d[29]), "+f"(d[30]), "+f"(d[31]), "+f"(d[32]), "+f"(d[33]), "+f"(d[34]), "+f"(d[35]), "+f"(d[36]), "+f"(d[37]), "+f"(d[38]), "+f"(d[39]), "+f"(d[40]), "+f"(d[41]), "+f"(d[42]), "+f"(d[43]), "+f"(d[44]), "+f"(d[45]), "+f"(d[46]), "+f"(d[47]), "+f"(d[48]), "+f"(d[49]), "+f"(d[50]), "+f"(d[51]), "+f"(d[52]), "+f"(d[53]), "+f"(d[54]), "+f"(d[55]), "+f"(d[56]), "+f"(d[57]), "+f"(d[58]), "+f"(d[59]), "+f"(d[60]), "+f"(d[61]), "+f"(d[62]), "+f"(d[63]), "+f"(d[64]), "+f"(d[65]), "+f"(d[66]), "+f"(d[67]), "+f"(d[68]), "+f"(d[69]), "+f"(d[70]), "+f"(d[71]), "+f"(d[72]), "+f"(d[73]), "+f"(d[74]), "+f"(d[75]), "+f"(d[76]), "+f"(d[77]), "+f"(d[78]), "+f"(d[79]), "+f"(d[80]), "+f"(d[81]), "+f"(d[82]), "+f"(d[83]), "+f"(d[84]), "+f"(d[85]), "+f"(d[86]), "+f"(d[87]), "+f"(d[88]), "+f"(d[89]), "+f"(d[90]), "+f"(d[91]), "+f"(d[92]), "+f"(d[93]), "+f"(d[94]), "+f"(d[95]), "+f"(d[96]), "+f"(d[97]), "+f"(d[98]), "+f"(d[99]), "+f"(d[100]), "+f"(d[101]), "+f"(d[102]), "+f"(d[103]), "+f"(d[104]), "+f"(d[105]), "+f"(d[106]), "+f"(d[107]), "+f"(d[108]), "+f"(d[109]), "+f"(d[110]), "+f"(d[111])
        : "l"(da), "l"(db), "r"(scaleD), "n"(TB));
}

constexpr int S1_STAGES = 5;
constexpr int S1_XN = 0;
constexpr int S1_B = 7 * 16384;
constexpr int STG = S1_B + S1_STAGES * 16384;
constexpr int S2_STAGES = 4;
constexpr int S2_STAGE = 49152;
constexpr int BAR = STG + 2 * 16384;
constexpr int BAR_F1 = BAR, BAR_E1 = BAR + 40, BAR_F2 = BAR + 80, BAR_E2 = BAR + 112, BAR_S1DONE = BAR + 144;
constexpr int BAR_SF = BAR + 152, BAR_SE = BAR + 168;
constexpr int SMEM_BYTES = BAR + 256 + 1024;
constexpr int TPITCH = 464;

__device__ __forceinline__ int n_passes(int j) { return j < 4 ? 2 : (j < 6 ? 3 : (j == 6 ? 11 : 10)); }
__device__ __forceinline__ int pass_slab(int j, int p) {
    if (p == 0) return j < 7 ? -1 : 0;
    if (p == 1) return 1 + j;
    if (p == 2) return 5 + j;
    return 13 + 2 * (p - 3) + (j - 6);
}

template <int TB>
__device__ __forceinline__ void s1_mainloop(float (&acc)[2][64], uint32_t sb, int idx, int lane, int handoff) {
    int st = idx % S1_STAGES;
    uint32_t ph = (idx / S1_STAGES) & 1;
    int prev = 0;
    uint64_t da = mkdesc(sb + S1_XN, 16, 1024);
    const uint64_t db0 = TB ? mkdesc(sb + S1_B, 8192, 1024) : mkdesc(sb + S1_B, 16, 1024);
#pragma unroll 1
    for (int kb = 0; kb < 7; kb++) {
        mbar_wait(sb + BAR_F1 + 8 * st, ph);
        if (kb == 6 && handoff) asm volatile("bar.arrive %0, 256;" ::"r"(handoff) : "memory");
        const uint64_t db = db0 + st * 1024;
        wg_arrive();
#pragma unroll
        for (int s = 0; s < 4; s++) {
            wgmma_n128<TB>(acc[0], da + s * 2, db + s * (TB ? 128 : 2), kb | s);
            wgmma_n128<TB>(acc[1], da + 512 + s * 2, db + s * (TB ? 128 : 2), kb | s);
        }
        wg_commit();
        wg_wait<1>();
        if (kb > 0 && lane == 0) mbar_arrive_both(sb + BAR_E1 + 8 * prev);
        prev = st;
        da += 1024;
        if (++st == S1_STAGES) { st = 0; ph ^= 1; }
    }
    wg_wait<0>();
    if (lane == 0) mbar_arrive_both(sb + BAR_E1 + 8 * prev);
}

template <int TB>
__device__ __forceinline__ void s2_mainloop(float (&acc)[112], uint32_t sb, int nkb, int wg, int lane) {
    int st = 0;
    uint32_t ph = 0;
    int prev = 0;
    const uint64_t da0 = mkdesc(sb + wg * 8192, 16, 1024);
    const uint64_t db0 = TB ? mkdesc(sb + 16384, 8192, 1024) : mkdesc(sb + 16384, 16, 1024);
#pragma unroll 1
    for (int i = 0; i < nkb; i++) {
        mbar_wait(sb + BAR_F2 + 8 * st, ph);
        const uint64_t da = da0 + st * (S2_STAGE / 16), db = db0 + st * (S2_STAGE / 16);
        wg_arrive();
#pragma unroll
        for (int s = 0; s < 4; s++) wgmma_n224<TB>(acc, da + s * 2, db + s * (TB ? 128 : 2), i | s);
        wg_commit();
        wg_wait<1>();
        if (i > 0 && lane == 0) mbar_arrive_both(sb + BAR_E2 + 8 * prev);
        prev = st;
        if (++st == S2_STAGES) { st = 0; ph ^= 1; }
    }
    wg_wait<0>();
    if (lane == 0) mbar_arrive_both(sb + BAR_E2 + 8 * prev);
}

struct Maps {
    CUtensorMap wg, wu, hre, him, h, abT_st, abT, sre, sim, wd;
};
struct Ptrs {
    const __nv_bfloat16 *x, *hre, *him, *wg, *wu, *wd;
    __nv_bfloat16* out;
};
__device__ __forceinline__ void mbar_arrive(uint32_t b) {
    asm volatile("mbarrier.arrive.shared::cta.b64 _, [%0];" ::"r"(b) : "memory");
}
__device__ __forceinline__ void l2_prefetch(const void* p, uint32_t bytes) {
    asm volatile("cp.async.bulk.prefetch.L2.global [%0], %1;" ::"l"(p), "r"(bytes) : "memory");
}
__device__ __forceinline__ void tma_prefetch(const CUtensorMap* m, int c0, int c1) {
    asm volatile("cp.async.bulk.prefetch.tensor.2d.L2.global.tile [%0, {%1, %2}];" ::"l"(m), "r"(c0), "r"(c1) : "memory");
}

__global__ void __launch_bounds__(384, 1)
fused_kernel(const __grid_constant__ Ptrs pt, const __grid_constant__ Maps tm) {
    extern __shared__ unsigned char smem_raw[];
    const uint32_t sb = (s2u(smem_raw) + 1023) & ~1023u;
    const int tid = threadIdx.x, lane = tid & 31;
    const int warp = __shfl_sync(0xffffffffu, tid >> 5, 0);
    const int rank = blockIdx.x & 1;
    const int cid = blockIdx.x >> 1;
    const int j = cid & 7;
    const int rb = (cid >> 3) * 2 + rank;
    const int npass = n_passes(j);
    const int n = j & 1;
    const int part = j >> 1;

    if (warp >= 8) {
        asm volatile("setmaxnreg.dec.sync.aligned.u32 40;");
        if (tid == 256) {
            TL(0, 0);
            for (int i = 0; i < S1_STAGES; i++) { mbar_init(sb + BAR_F1 + 8 * i, 1); mbar_init(sb + BAR_E1 + 8 * i, 8); }
            for (int i = 0; i < S2_STAGES; i++) { mbar_init(sb + BAR_F2 + 8 * i, 1); mbar_init(sb + BAR_E2 + 8 * i, 16); }
            mbar_init(sb + BAR_S1DONE, 16);
            for (int i = 0; i < 2; i++) { mbar_init(sb + BAR_SF + 8 * i, 1); mbar_init(sb + BAR_SE + 8 * i, 1); }
            asm volatile("fence.mbarrier_init.release.cluster;" ::: "memory");
        }
        __syncwarp();
        cluster_sync();
        if (warp == 8) {
            if (lane == 0) {
                int st = 0;
                uint32_t ph = 1;
                for (int p = 0; p < npass; p++) {
                    const int slab = pass_slab(j, p);
                    for (int kb = 0; kb < 7; kb++) {
                        mbar_wait(sb + BAR_E1 + 8 * st, ph);
                        const uint32_t dst = sb + S1_B + st * 16384 + rank * 8192;
                        const uint32_t fb = sb + BAR_F1 + 8 * st;
                        mbar_expect(fb, 16384);
                        if (slab >= 0) {
                            tma_load_mc(dst, rank ? &tm.wu : &tm.wg, fb, slab * 64, kb * 64);
                        } else {
                            const int a = 2 * j + rank;
                            tma_load_mc(dst, a < 7 ? &tm.hre : &tm.him, fb, kb * 64, (a < 7 ? a : a - 7) * 64);
                        }
                        if (++st == S1_STAGES) { st = 0; ph ^= 1; }
                        if (p == 0 && kb == S1_STAGES - 1) {
                            const int b = blockIdx.x;
                            l2_prefetch((const char*)pt.hre + b * 3136, 3136);
                            l2_prefetch((const char*)pt.him + b * 3136, 3136);
                            l2_prefetch((const char*)pt.wg + b * 12544, 12544);
                            l2_prefetch((const char*)pt.wu + b * 12544, 12544);
                            l2_prefetch((const char*)pt.wd + b * 12544, 12544);
                        }
                        if (p == 1 && part < 2) {
                            const CUtensorMap* ma = part ? &tm.sim : &tm.sre;
                            for (int q = kb; q < 16; q += 7) tma_prefetch(ma, (2 * q + n) * 64, rb * 128);
                        }
                    }
                }
                if (part < 3) {
                    mbar_wait(sb + BAR_S1DONE, 0);
                    TL(0, 24);
                    st = 0; ph = 1;
                    if (part < 2) {
                        const CUtensorMap* ma = part ? &tm.sim : &tm.sre;
                        for (int g = 0; g < 32; g++) {
                            mbar_wait(sb + BAR_E2 + 8 * st, ph);
                            const uint32_t dst = sb + st * S2_STAGE;
                            const uint32_t fb = sb + BAR_F2 + 8 * st;
                            mbar_expect(fb, 16384 + 28672);
                            tma_load(dst, ma, fb, g * 64, rb * 128);
                            if ((g & 1) == 0) flag_wait(&g_fl.ab[g >> 1], 7);
                            tma_load_mc(dst + 16384 + rank * 14336, &tm.abT, fb, g * 64, part * 448 + n * 224 + rank * 112);
                            if (++st == S2_STAGES) { st = 0; ph ^= 1; }
                        }
                    } else {
                        for (int g = 0; g < 28; g++) {
                            mbar_wait(sb + BAR_E2 + 8 * st, ph);
                            const uint32_t dst = sb + st * S2_STAGE;
                            const uint32_t fb = sb + BAR_F2 + 8 * st;
                            mbar_expect(fb, 16384 + 32768);
                            tma_load_mc(dst + 16384 + (2 * rank) * 8192, &tm.wd, fb, n * 224 + (2 * rank) * 64, g * 64);
                            tma_load_mc(dst + 16384 + (2 * rank + 1) * 8192, &tm.wd, fb, n * 224 + (2 * rank + 1) * 64, g * 64);
                            flag_wait(&g_fl.h[rb * 28 + g], 1);
                            tma_load(dst, &tm.h, fb, g * 64, rb * 128);
                            if (++st == S2_STAGES) { st = 0; ph ^= 1; }
                        }
                    }
                }
            }
        } else if (warp == 9) {
            if (lane == 0) {
                uint32_t ph0 = 0, ph1 = 0;
                for (int p = 0; p < npass; p++) {
                    const int slab = pass_slab(j, p);
                    if (slab < 0) {
                        for (int hf = 0; hf < 2; hf++) {
                            mbar_wait(sb + BAR_SF + 8 * hf, 0);
                            tma_store(&tm.abT_st, sb + STG + hf * 16384, rb * 128, (2 * j + hf) * 64);
                            tma_store(&tm.abT_st, sb + STG + hf * 16384 + 8192, rb * 128 + 64, (2 * j + hf) * 64);
                            bulk_commit();
                        }
                        ph0 ^= 1; ph1 ^= 1;
                        bulk_wait_read0();
                        mbar_arrive(sb + BAR_SE);
                        mbar_arrive(sb + BAR_SE + 8);
                        bulk_wait0();
                        flag_signal(&g_fl.ab[rb]);
                    } else {
                        const int b = p & 1;
                        mbar_wait(sb + BAR_SF + 8 * b, b ? ph1 : ph0);
                        if (b) ph1 ^= 1; else ph0 ^= 1;
                        tma_store(&tm.h, sb + STG + b * 16384, slab * 64, rb * 128);
                        bulk_commit();
                        bulk_wait_read0();
                        mbar_arrive(sb + BAR_SE + 8 * b);
                        bulk_wait0();
                        flag_signal(&g_fl.h[rb * 28 + slab]);
                    }
                }
            }
        }
        __syncwarp();
    } else {
        asm volatile("setmaxnreg.inc.sync.aligned.u32 232;");
        {
            const int l8 = lane & 7, sub = lane >> 3;
            uint4 v[4][7];
#pragma unroll
            for (int it = 0; it < 4; it++) {
                const uint4* src = reinterpret_cast<const uint4*>(pt.x + (size_t)(rb * 128 + warp * 16 + it * 4 + sub) * D_) + l8;
#pragma unroll
                for (int i = 0; i < 7; i++) v[it][i] = __ldg(src + i * 8);
            }
            cluster_sync();
            if (tid == 0) TL(0, 1);
#pragma unroll
            for (int it = 0; it < 4; it++) {
                const int row = warp * 16 + it * 4 + sub;
                float s0 = 0.f, s1 = 0.f;
#pragma unroll
                for (int i = 0; i < 7; i++) {
                    s0 += (bf_lo(v[it][i].x) + bf_hi(v[it][i].x)) + (bf_lo(v[it][i].y) + bf_hi(v[it][i].y));
                    s1 += (bf_lo(v[it][i].z) + bf_hi(v[it][i].z)) + (bf_lo(v[it][i].w) + bf_hi(v[it][i].w));
                }
                float s = s0 + s1;
                s += __shfl_xor_sync(0xffffffffu, s, 1);
                s += __shfl_xor_sync(0xffffffffu, s, 2);
                s += __shfl_xor_sync(0xffffffffu, s, 4);
                if (it == 0 && tid == 0) TL(0, 3);
                const float mean = s * (1.0f / D_);
                float q0 = 0.f, q1 = 0.f;
#pragma unroll
                for (int i = 0; i < 7; i++) {
                    const uint32_t w[4] = {v[it][i].x, v[it][i].y, v[it][i].z, v[it][i].w};
#pragma unroll
                    for (int c = 0; c < 4; c++) {
                        const float d0 = bf_lo(w[c]) - mean, d1 = bf_hi(w[c]) - mean;
                        q0 = fmaf(d0, d0, q0);
                        q1 = fmaf(d1, d1, q1);
                    }
                }
                float q = q0 + q1;
                q += __shfl_xor_sync(0xffffffffu, q, 1);
                q += __shfl_xor_sync(0xffffffffu, q, 2);
                q += __shfl_xor_sync(0xffffffffu, q, 4);
                const float var = rbf(q * (1.0f / D_));
                const float den = rbf(sqrtf(rbf(var + 1e-5f)));
                const float rinv = 1.0f / den;
                const float rhi = rbf(rinv);
                const uint32_t m2 = pack_bf16(mean, mean), rhi2 = pack_bf16(rhi, rhi), rlo2 = pack_bf16(rinv - rhi, rinv - rhi);
                const uint32_t dst = sb + S1_XN + row * 128 + ((l8 ^ (row & 7)) << 4);
#pragma unroll
                for (int i = 0; i < 7; i++) {
                    const uint32_t w[4] = {v[it][i].x, v[it][i].y, v[it][i].z, v[it][i].w};
                    uint32_t o[4];
#pragma unroll
                    for (int c = 0; c < 4; c++) {
                        const uint32_t xc = hsub2(w[c], m2);
                        o[c] = hfma2(xc, rhi2, hmul2(xc, rlo2));
                    }
                    asm volatile("st.shared.v4.b32 [%0], {%1, %2, %3, %4};" ::"r"(dst + i * 16384), "r"(o[0]), "r"(o[1]), "r"(o[2]), "r"(o[3]) : "memory");
                }
            }
            fence_async();
            bar_sync(1, 256);
            if (tid == 0) TL(0, 2);
        }
        const int wg = warp >> 2, wl = warp & 3, wtid = tid & 127;
        {
            float acc[2][64];
            const uint32_t stg = sb + STG + wg * 16384;
            uint32_t se_ph = (wg == 1 && j < 7) ? 0 : 1;
            for (int p = wg; p < npass; p += 2) {
                const int slab = pass_slab(j, p);
                if (p > 0) bar_sync(4 + (p & 1), 256);
                const int handoff = (p + 1 < npass) ? 4 + ((p + 1) & 1) : 0;
                if (slab >= 0) s1_mainloop<1>(acc, sb, p * 7, lane, handoff);
                else s1_mainloop<0>(acc, sb, p * 7, lane, handoff);
                if (p + 2 >= npass && lane == 0) mbar_arrive_both(sb + BAR_S1DONE);
                if (wtid == 0 && p < 4) TL(0, 4 + p);

                if (slab >= 0) {
                    mbar_wait(sb + BAR_SE + 8 * wg, se_ph);
                    se_ph ^= 1;
#pragma unroll
                    for (int mh = 0; mh < 2; mh++) {
                        const int row = mh * 64 + wl * 16 + (lane & 7) + ((lane >> 3) & 1) * 8;
#pragma unroll
                        for (int jj = 0; jj < 8; jj += 2) {
                            uint32_t r[4];
#pragma unroll
                            for (int t = 0; t < 4; t++) {
                                const int o = (jj + (t >> 1)) * 4 + (t & 1) * 2;
                                const uint32_t g2 = pack_bf16(acc[mh][o], acc[mh][o + 1]);
                                const uint32_t u2 = pack_bf16(acc[mh][32 + o], acc[mh][32 + o + 1]);
                                const uint32_t a2 = pack_bf16(gelu_tanh(bf_lo(g2)), gelu_tanh(bf_hi(g2)));
                                r[t] = hmul2(a2, u2);
                            }
                            const int chunk = jj + (lane >> 4);
                            stmat4(stg + row * 128 + ((chunk ^ (row & 7)) << 4), r[0], r[1], r[2], r[3]);
                        }
                    }
                    fence_async();
                    bar_sync(2 + wg, 128);
                    if (wtid == 0) mbar_arrive(sb + BAR_SF + 8 * wg);
                } else {
                    se_ph ^= 1;
#pragma unroll
                    for (int hf = 0; hf < 2; hf++) {
#pragma unroll
                        for (int mh = 0; mh < 2; mh++) {
#pragma unroll
                            for (int jj = 0; jj < 8; jj += 2) {
                                uint32_t r[4];
#pragma unroll
                                for (int t = 0; t < 4; t++) {
                                    const int o = hf * 32 + (jj + (t >> 1)) * 4 + (t & 1) * 2;
                                    r[t] = pack_bf16(acc[mh][o], acc[mh][o + 1]);
                                }
                                const int e = 8 * (jj + (lane >> 4)) + (lane & 7);
                                const int sc = 2 * wl + ((lane >> 3) & 1);
                                stmat4t(sb + STG + hf * 16384 + mh * 8192 + e * 128 + ((sc ^ (e & 7)) << 4), r[0], r[1], r[2], r[3]);
                            }
                        }
                        fence_async();
                        bar_sync(2 + wg, 128);
                        if (wtid == 0) mbar_arrive(sb + BAR_SF + 8 * hf);
                    }
                }
                if (wtid == 0 && p < 4) TL(0, 10 + p);
            }
        }
        if (wtid == 0) TL(0, 20 + wg);
        if (part < 3) {
            {
                float acc[112];
                if (part < 2) s2_mainloop<0>(acc, sb, 32, wg, lane);
                else s2_mainloop<1>(acc, sb, 28, wg, lane);
                if (tid == 0) TL(0, 25);
                bar_sync(1, 256);
                const uint32_t a0 = sb + (wg * 64 + wl * 16 + (lane & 7) + ((lane >> 3) & 1) * 8) * TPITCH + (lane >> 4) * 16;
                if (part < 2) {
#pragma unroll
                    for (int q = 0; q < 14; q++)
                        stmat4(a0 + q * 32, pack_bf16(acc[8 * q], acc[8 * q + 1]), pack_bf16(acc[8 * q + 2], acc[8 * q + 3]),
                               pack_bf16(acc[8 * q + 4], acc[8 * q + 5]), pack_bf16(acc[8 * q + 6], acc[8 * q + 7]));
                } else {
#pragma unroll
                    for (int q = 0; q < 14; q++) {
                        uint32_t o[4];
#pragma unroll
                        for (int t = 0; t < 4; t++) {
                            const uint32_t f2 = pack_bf16(acc[8 * q + 2 * t], acc[8 * q + 2 * t + 1]);
                            o[t] = pack_bf16(silu(bf_lo(f2)), silu(bf_hi(f2)));
                        }
                        stmat4(a0 + q * 32, o[0], o[1], o[2], o[3]);
                    }
                }
            }
            if (part < 2) {
                bar_sync(1, 256);
                __nv_bfloat16* dst = g_y + (size_t)(part * S_ + rb * 128) * D_ + n * 224;
#pragma unroll
                for (int i = 0; i < 14; i++) {
                    const int idx = tid + 256 * i, row = idx / 28, c = idx % 28;
                    uint4 v;
                    asm volatile("ld.shared.v4.b32 {%0, %1, %2, %3}, [%4];" : "=r"(v.x), "=r"(v.y), "=r"(v.z), "=r"(v.w) : "r"(sb + row * TPITCH + c * 16));
                    __stcg(reinterpret_cast<uint4*>(dst + row * D_ + c * 8), v);
                }
                __threadfence();
                bar_sync(1, 256);
                if (tid == 0) asm volatile("red.release.gpu.global.add.u32 [%0], 1;" ::"l"(&g_fl.y[rb * 2 + n]) : "memory");
            } else {
                const size_t base = (size_t)(rb * 128) * D_ + n * 224;
                uint4 xv[14];
#pragma unroll
                for (int i = 0; i < 14; i++) {
                    const int idx = tid + 256 * i, row = idx / 28, c = idx % 28;
                    xv[i] = __ldg(reinterpret_cast<const uint4*>(pt.x + base + row * D_ + c * 8));
                }
                if (tid == 0) flag_wait(&g_fl.y[rb * 2 + n], 2);
                bar_sync(1, 256);
                if (tid == 0) TL(0, 26);
                uint4 yr[14], yi[14];
#pragma unroll
                for (int i = 0; i < 14; i++) {
                    const int idx = tid + 256 * i, row = idx / 28, c = idx % 28;
                    yr[i] = __ldcg(reinterpret_cast<const uint4*>(g_y + base + row * D_ + c * 8));
                    yi[i] = __ldcg(reinterpret_cast<const uint4*>(g_y + (size_t)S_ * D_ + base + row * D_ + c * 8));
                }
#pragma unroll
                for (int i = 0; i < 14; i++) {
                    const int idx = tid + 256 * i, row = idx / 28, c = idx % 28;
                    uint4 g, o;
                    asm volatile("ld.shared.v4.b32 {%0, %1, %2, %3}, [%4];" : "=r"(g.x), "=r"(g.y), "=r"(g.z), "=r"(g.w) : "r"(sb + row * TPITCH + c * 16));
                    o.x = hadd2(xv[i].x, hmul2(hsub2(yr[i].x, yi[i].x), g.x));
                    o.y = hadd2(xv[i].y, hmul2(hsub2(yr[i].y, yi[i].y), g.y));
                    o.z = hadd2(xv[i].z, hmul2(hsub2(yr[i].z, yi[i].z), g.z));
                    o.w = hadd2(xv[i].w, hmul2(hsub2(yr[i].w, yi[i].w), g.w));
                    *reinterpret_cast<uint4*>(pt.out + base + row * D_ + c * 8) = o;
                }
            }
        }
    }
    cluster_sync();
    if (tid == 0) {
        TL(0, 30);
        __threadfence();
        if (atomicAdd(&g_fl.done, 1u) == gridDim.x - 1) {
            unsigned int* f = reinterpret_cast<unsigned int*>(&g_fl);
            for (int i = 0; i < (int)(sizeof(Flags) / 4); i++) f[i] = 0;
        }
    }
}

typedef CUresult (*EncFn)(CUtensorMap*, CUtensorMapDataType, cuuint32_t, void*, const cuuint64_t*, const cuuint64_t*,
                          const cuuint32_t*, const cuuint32_t*, CUtensorMapInterleave, CUtensorMapSwizzle,
                          CUtensorMapL2promotion, CUtensorMapFloatOOBfill);

void make_map(EncFn enc, CUtensorMap* m, const void* ptr, int rows, int cols, int box_rows, int box_cols, bool swz = true) {
    cuuint64_t gd[2] = {(cuuint64_t)cols, (cuuint64_t)rows};
    cuuint64_t gs[1] = {(cuuint64_t)cols * 2};
    cuuint32_t bx[2] = {(cuuint32_t)box_cols, (cuuint32_t)box_rows};
    cuuint32_t es[2] = {1, 1};
    enc(m, CU_TENSOR_MAP_DATA_TYPE_BFLOAT16, 2, const_cast<void*>(ptr), gd, gs, bx, es, CU_TENSOR_MAP_INTERLEAVE_NONE,
        swz ? CU_TENSOR_MAP_SWIZZLE_128B : CU_TENSOR_MAP_SWIZZLE_NONE, CU_TENSOR_MAP_L2_PROMOTION_L2_128B,
        CU_TENSOR_MAP_FLOAT_OOB_FILL_NONE);
}

}

extern "C" void kernel_launch(void* const* d_in, const int* in_sizes, int n_in, void* d_out, int out_size) {
    Ptrs pt;
    pt.x = (const __nv_bfloat16*)d_in[0];
    pt.hre = (const __nv_bfloat16*)d_in[3];
    pt.him = (const __nv_bfloat16*)d_in[4];
    pt.wg = (const __nv_bfloat16*)d_in[6];
    pt.wu = (const __nv_bfloat16*)d_in[7];
    pt.wd = (const __nv_bfloat16*)d_in[8];
    pt.out = (__nv_bfloat16*)d_out;

    void* fn = nullptr;
    cudaDriverEntryPointQueryResult qr;
    cudaGetDriverEntryPoint("cuTensorMapEncodeTiled", &fn, cudaEnableDefault, &qr);
    EncFn enc = (EncFn)fn;
    void *p_abT, *p_h;
    cudaGetSymbolAddress(&p_abT, g_abT);
    cudaGetSymbolAddress(&p_h, g_h);

    Maps tm;
    make_map(enc, &tm.wg, d_in[6], D_, F_, 64, 64);
    make_map(enc, &tm.wu, d_in[7], D_, F_, 64, 64);
    make_map(enc, &tm.hre, d_in[3], D_, D_, 64, 64);
    make_map(enc, &tm.him, d_in[4], D_, D_, 64, 64);
    make_map(enc, &tm.h, p_h, S_, F_, 128, 64);
    make_map(enc, &tm.abT_st, p_abT, 896, S_, 64, 64);
    make_map(enc, &tm.abT, p_abT, 896, S_, 112, 64);
    make_map(enc, &tm.sre, d_in[1], S_, S_, 128, 64);
    make_map(enc, &tm.sim, d_in[2], S_, S_, 128, 64);
    make_map(enc, &tm.wd, d_in[8], F_, D_, 64, 64);

    cudaFuncSetAttribute(fused_kernel, cudaFuncAttributeMaxDynamicSharedMemorySize, SMEM_BYTES);

    cudaLaunchAttribute at[1];
    at[0].id = cudaLaunchAttributeClusterDimension;
    at[0].val.clusterDim.x = 2; at[0].val.clusterDim.y = 1; at[0].val.clusterDim.z = 1;
    cudaLaunchConfig_t cfg = {};
    cfg.gridDim = dim3(128); cfg.blockDim = dim3(384); cfg.stream = cudaStreamPerThread;
    cfg.attrs = at; cfg.numAttrs = 1;
    cfg.dynamicSmemBytes = SMEM_BYTES;
    cudaLaunchKernelEx(&cfg, fused_kernel, pt, tm);
}
```

```cpp
#include <cuda_runtime.h>
#include <cuda_bf16.h>
#include <cuda.h>
#include <stdint.h>

namespace {

constexpr int S_ = 2048, D_ = 448, F_ = 1792;

__device__ __align__(1024) __nv_bfloat16 g_abT[896 * 2048];
__device__ __align__(1024) __nv_bfloat16 g_h[2048 * 1792];
__device__ __align__(1024) __nv_bfloat16 g_y[2 * 2048 * 448];
struct Flags {
    unsigned int ab[16];
    unsigned int h[16 * 28];
    unsigned int y[32];
    unsigned int done;
};
__device__ Flags g_fl;

#define TL(k, i) do {} while (0)
__device__ __forceinline__ uint32_t s2u(const void* p) { return (uint32_t)__cvta_generic_to_shared(p); }
__device__ __forceinline__ void mbar_init(uint32_t b, int c) {
    asm volatile("mbarrier.init.shared::cta.b64 [%0], %1;" ::"r"(b), "r"(c));
}
__device__ __forceinline__ void mbar_expect(uint32_t b, uint32_t bytes) {
    asm volatile("mbarrier.arrive.expect_tx.shared::cta.b64 _, [%0], %1;" ::"r"(b), "r"(bytes) : "memory");
}
__device__ __forceinline__ void mbar_wait(uint32_t b, uint32_t ph) {
    uint32_t ok;
    do {
        asm volatile("{\n.reg .pred p;\nmbarrier.try_wait.parity.shared::cta.b64 p, [%1], %2;\nselp.u32 %0, 1, 0, p;\n}"
                     : "=r"(ok) : "r"(b), "r"(ph) : "memory");
    } while (!ok);
}
__device__ __forceinline__ void mbar_arrive_both(uint32_t b) {
    asm volatile("{\n.reg .b32 r0, r1;\n"
                 "mapa.shared::cluster.u32 r0, %0, 0;\n"
                 "mapa.shared::cluster.u32 r1, %0, 1;\n"
                 "mbarrier.arrive.shared::cluster.b64 _, [r0];\n"
                 "mbarrier.arrive.shared::cluster.b64 _, [r1];\n}"
                 ::"r"(b) : "memory");
}
__device__ __forceinline__ void tma_load(uint32_t dst, const CUtensorMap* m, uint32_t bar, int c0, int c1) {
    asm volatile("cp.async.bulk.tensor.2d.shared::cluster.global.mbarrier::complete_tx::bytes [%0], [%1, {%3, %4}], [%2];"
                 ::"r"(dst), "l"(m), "r"(bar), "r"(c0), "r"(c1) : "memory");
}
__device__ __forceinline__ void tma_load_mc(uint32_t dst, const CUtensorMap* m, uint32_t bar, int c0, int c1) {
    asm volatile("cp.async.bulk.tensor.2d.shared::cluster.global.mbarrier::complete_tx::bytes.multicast::cluster [%0], [%1, {%3, %4}], [%2], %5;"
                 ::"r"(dst), "l"(m), "r"(bar), "r"(c0), "r"(c1), "h"((uint16_t)3) : "memory");
}
__device__ __forceinline__ void tma_store(const CUtensorMap* m, uint32_t src, int c0, int c1) {
    asm volatile("cp.async.bulk.tensor.2d.global.shared::cta.bulk_group [%0, {%2, %3}], [%1];"
                 ::"l"(m), "r"(src), "r"(c0), "r"(c1) : "memory");
}
__device__ __forceinline__ void bulk_commit() { asm volatile("cp.async.bulk.commit_group;" ::: "memory"); }
__device__ __forceinline__ void bulk_wait_read0() { asm volatile("cp.async.bulk.wait_group.read 0;" ::: "memory"); }
__device__ __forceinline__ void bulk_wait0() { asm volatile("cp.async.bulk.wait_group 0;" ::: "memory"); }
__device__ __forceinline__ void fence_async() { asm volatile("fence.proxy.async.shared::cta;" ::: "memory"); }
__device__ __forceinline__ void fence_async_all() { asm volatile("fence.proxy.async;" ::: "memory"); }
__device__ __forceinline__ void cluster_sync() {
    asm volatile("barrier.cluster.arrive.release.aligned;\nbarrier.cluster.wait.acquire.aligned;" ::: "memory");
}
__device__ __forceinline__ void bar_sync(int id, int n) { asm volatile("bar.sync %0, %1;" ::"r"(id), "r"(n) : "memory"); }
__device__ __forceinline__ void wg_arrive() { asm volatile("wgmma.fence.sync.aligned;" ::: "memory"); }
__device__ __forceinline__ void wg_commit() { asm volatile("wgmma.commit_group.sync.aligned;" ::: "memory"); }
template <int N> __device__ __forceinline__ void wg_wait() { asm volatile("wgmma.wait_group.sync.aligned %0;" ::"n"(N) : "memory"); }
__device__ __forceinline__ void stmat4(uint32_t a, uint32_t r0, uint32_t r1, uint32_t r2, uint32_t r3) {
    asm volatile("stmatrix.sync.aligned.m8n8.x4.shared.b16 [%0], {%1, %2, %3, %4};" ::"r"(a), "r"(r0), "r"(r1), "r"(r2), "r"(r3) : "memory");
}
__device__ __forceinline__ void stmat4t(uint32_t a, uint32_t r0, uint32_t r1, uint32_t r2, uint32_t r3) {
    asm volatile("stmatrix.sync.aligned.m8n8.x4.trans.shared.b16 [%0], {%1, %2, %3, %4};" ::"r"(a), "r"(r0), "r"(r1), "r"(r2), "r"(r3) : "memory");
}
__device__ __forceinline__ void ldmat4(uint32_t a, uint32_t (&r)[4]) {
    asm volatile("ldmatrix.sync.aligned.m8n8.x4.shared.b16 {%0, %1, %2, %3}, [%4];"
                 : "=r"(r[0]), "=r"(r[1]), "=r"(r[2]), "=r"(r[3]) : "r"(a) : "memory");
}
__device__ __forceinline__ void flag_add(unsigned int* f) {
    asm volatile("red.release.gpu.global.add.u32 [%0], 1;" ::"l"(f) : "memory");
}
__device__ __forceinline__ void flag_wait(const unsigned int* f, unsigned int target) {
    unsigned int v;
    int spins = 0;
    while (true) {
        asm volatile("ld.acquire.gpu.global.u32 %0, [%1];" : "=r"(v) : "l"(f) : "memory");
        if (v >= target || ++spins > (1 << 22)) break;
    }
}
__device__ __forceinline__ void quad_transpose(uint32_t (&r)[4], int q) {
    const bool o1 = q & 1, o2 = q & 2;
    uint32_t a = o1 ? r[0] : r[1], b = o1 ? r[2] : r[3];
    a = __shfl_xor_sync(0xffffffffu, a, 1);
    b = __shfl_xor_sync(0xffffffffu, b, 1);
    if (o1) { r[0] = a; r[2] = b; } else { r[1] = a; r[3] = b; }
    a = o2 ? r[0] : r[2]; b = o2 ? r[1] : r[3];
    a = __shfl_xor_sync(0xffffffffu, a, 2);
    b = __shfl_xor_sync(0xffffffffu, b, 2);
    if (o2) { r[0] = a; r[1] = b; } else { r[2] = a; r[3] = b; }
}
__device__ __forceinline__ uint32_t movmat_t(uint32_t v) {
    uint32_t r;
    asm volatile("movmatrix.sync.aligned.m8n8.trans.b16 %0, %1;" : "=r"(r) : "r"(v));
    return r;
}
__device__ __forceinline__ uint64_t mkdesc(uint32_t addr, uint32_t lbo, uint32_t sbo) {
    return (uint64_t)((addr & 0x3FFFF) >> 4) | ((uint64_t)(lbo >> 4) << 16) | ((uint64_t)(sbo >> 4) << 32) | (1ull << 62);
}
__device__ __forceinline__ uint32_t pack_bf16(float lo, float hi) {
    uint32_t r;
    asm("cvt.rn.bf16x2.f32 %0, %1, %2;" : "=r"(r) : "f"(hi), "f"(lo));
    return r;
}
__device__ __forceinline__ uint32_t hsub2(uint32_t a, uint32_t b) { uint32_t r; asm("sub.rn.bf16x2 %0, %1, %2;" : "=r"(r) : "r"(a), "r"(b)); return r; }
__device__ __forceinline__ uint32_t hadd2(uint32_t a, uint32_t b) { uint32_t r; asm("add.rn.bf16x2 %0, %1, %2;" : "=r"(r) : "r"(a), "r"(b)); return r; }
__device__ __forceinline__ uint32_t hmul2(uint32_t a, uint32_t b) { uint32_t r; asm("mul.rn.bf16x2 %0, %1, %2;" : "=r"(r) : "r"(a), "r"(b)); return r; }
__device__ __forceinline__ uint32_t hfma2(uint32_t a, uint32_t b, uint32_t c) { uint32_t r; asm("fma.rn.bf16x2 %0, %1, %2, %3;" : "=r"(r) : "r"(a), "r"(b), "r"(c)); return r; }
__device__ __forceinline__ float bf_lo(uint32_t u) { return __uint_as_float(u << 16); }
__device__ __forceinline__ float bf_hi(uint32_t u) { return __uint_as_float(u & 0xffff0000u); }
__device__ __forceinline__ float rbf(float v) { return __bfloat162float(__float2bfloat16_rn(v)); }
__device__ __forceinline__ float tanh_fast(float x) { float r; asm("tanh.approx.f32 %0, %1;" : "=f"(r) : "f"(x)); return r; }
__device__ __forceinline__ float gelu_tanh(float x) {
    float u = x * fmaf(x * x, 0.0356774081f, 0.7978845608f);
    float hx = 0.5f * x;
    return fmaf(hx, tanh_fast(u), hx);
}
__device__ __forceinline__ float silu(float f) { return __fdividef(f, 1.0f + __expf(-f)); }

template <int TB>
__device__ __forceinline__ void wgmma_n128(float (&d)[64], uint64_t da, uint64_t db, int scaleD) {
    asm volatile("{\n.reg .pred p;\nsetp.ne.b32 p, %66, 0;\n"
        "wgmma.mma_async.sync.aligned.m64n128k16.f32.bf16.bf16 {%0, %1, %2, %3, %4, %5, %6, %7, %8, %9, %10, %11, %12, %13, %14, %15, %16, %17, %18, %19, %20, %21, %22, %23, %24, %25, %26, %27, %28, %29, %30, %31, %32, %33, %34, %35, %36, %37, %38, %39, %40, %41, %42, %43, %44, %45, %46, %47, %48, %49, %50, %51, %52, %53, %54, %55, %56, %57, %58, %59, %60, %61, %62, %63}, %64, %65, p, 1, 1, 0, %67;\n}\n"
        : "+f"(d[0]), "+f"(d[1]), "+f"(d[2]), "+f"(d[3]), "+f"(d[4]), "+f"(d[5]), "+f"(d[6]), "+f"(d[7]), "+f"(d[8]), "+f"(d[9]), "+f"(d[10]), "+f"(d[11]), "+f"(d[12]), "+f"(d[13]), "+f"(d[14]), "+f"(d[15]), "+f"(d[16]), "+f"(d[17]), "+f"(d[18]), "+f"(d[19]), "+f"(d[20]), "+f"(d[21]), "+f"(d[22]), "+f"(d[23]), "+f"(d[24]), "+f"(d[25]), "+f"(d[26]), "+f"(d[27]), "+f"(d[28]), "+f"(d[29]), "+f"(d[30]), "+f"(d[31]), "+f"(d[32]), "+f"(d[33]), "+f"(d[34]), "+f"(d[35]), "+f"(d[36]), "+f"(d[37]), "+f"(d[38]), "+f"(d[39]), "+f"(d[40]), "+f"(d[41]), "+f"(d[42]), "+f"(d[43]), "+f"(d[44]), "+f"(d[45]), "+f"(d[46]), "+f"(d[47]), "+f"(d[48]), "+f"(d[49]), "+f"(d[50]), "+f"(d[51]), "+f"(d[52]), "+f"(d[53]), "+f"(d[54]), "+f"(d[55]), "+f"(d[56]), "+f"(d[57]), "+f"(d[58]), "+f"(d[59]), "+f"(d[60]), "+f"(d[61]), "+f"(d[62]), "+f"(d[63])
        : "l"(da), "l"(db), "r"(scaleD), "n"(TB));
}
template <int TB>
__device__ __forceinline__ void wgmma_n224(float (&d)[112], uint64_t da, uint64_t db, int scaleD) {
    asm volatile("{\n.reg .pred p;\nsetp.ne.b32 p, %114, 0;\n"
        "wgmma.mma_async.sync.aligned.m64n224k16.f32.bf16.bf16 {%0, %1, %2, %3, %4, %5, %6, %7, %8, %9, %10, %11, %12, %13, %14, %15, %16, %17, %18, %19, %20, %21, %22, %23, %24, %25, %26, %27, %28, %29, %30, %31, %32, %33, %34, %35, %36, %37, %38, %39, %40, %41, %42, %43, %44, %45, %46, %47, %48, %49, %50, %51, %52, %53, %54, %55, %56, %57, %58, %59, %60, %61, %62, %63, %64, %65, %66, %67, %68, %69, %70, %71, %72, %73, %74, %75, %76, %77, %78, %79, %80, %81, %82, %83, %84, %85, %86, %87, %88, %89, %90, %91, %92, %93, %94, %95, %96, %97, %98, %99, %100, %101, %102, %103, %104, %105, %106, %107, %108, %109, %110, %111}, %112, %113, p, 1, 1, 0, %115;\n}\n"
        : "+f"(d[0]), "+f"(d[1]), "+f"(d[2]), "+f"(d[3]), "+f"(d[4]), "+f"(d[5]), "+f"(d[6]), "+f"(d[7]), "+f"(d[8]), "+f"(d[9]), "+f"(d[10]), "+f"(d[11]), "+f"(d[12]), "+f"(d[13]), "+f"(d[14]), "+f"(d[15]), "+f"(d[16]), "+f"(d[17]), "+f"(d[18]), "+f"(d[19]), "+f"(d[20]), "+f"(d[21]), "+f"(d[22]), "+f"(d[23]), "+f"(d[24]), "+f"(d[25]), "+f"(d[26]), "+f"(d[27]), "+f"(d[28]), "+f"(d[29]), "+f"(d[30]), "+f"(d[31]), "+f"(d[32]), "+f"(d[33]), "+f"(d[34]), "+f"(d[35]), "+f"(d[36]), "+f"(d[37]), "+f"(d[38]), "+f"(d[39]), "+f"(d[40]), "+f"(d[41]), "+f"(d[42]), "+f"(d[43]), "+f"(d[44]), "+f"(d[45]), "+f"(d[46]), "+f"(d[47]), "+f"(d[48]), "+f"(d[49]), "+f"(d[50]), "+f"(d[51]), "+f"(d[52]), "+f"(d[53]), "+f"(d[54]), "+f"(d[55]), "+f"(d[56]), "+f"(d[57]), "+f"(d[58]), "+f"(d[59]), "+f"(d[60]), "+f"(d[61]), "+f"(d[62]), "+f"(d[63]), "+f"(d[64]), "+f"(d[65]), "+f"(d[66]), "+f"(d[67]), "+f"(d[68]), "+f"(d[69]), "+f"(d[70]), "+f"(d[71]), "+f"(d[72]), "+f"(d[73]), "+f"(d[74]), "+f"(d[75]), "+f"(d[76]), "+f"(d[77]), "+f"(d[78]), "+f"(d[79]), "+f"(d[80]), "+f"(d[81]), "+f"(d[82]), "+f"(d[83]), "+f"(d[84]), "+f"(d[85]), "+f"(d[86]), "+f"(d[87]), "+f"(d[88]), "+f"(d[89]), "+f"(d[90]), "+f"(d[91]), "+f"(d[92]), "+f"(d[93]), "+f"(d[94]), "+f"(d[95]), "+f"(d[96]), "+f"(d[97]), "+f"(d[98]), "+f"(d[99]), "+f"(d[100]), "+f"(d[101]), "+f"(d[102]), "+f"(d[103]), "+f"(d[104]), "+f"(d[105]), "+f"(d[106]), "+f"(d[107]), "+f"(d[108]), "+f"(d[109]), "+f"(d[110]), "+f"(d[111])
        : "l"(da), "l"(db), "r"(scaleD), "n"(TB));
}

constexpr int S1_STAGES = 7;
constexpr int S1_XN = 0;
constexpr int S1_B = 7 * 16384;
constexpr int Y_STAGES = 5, Y_STAGE = 45056;
constexpr int F_STAGES = 4, F_STAGE = 49152;
constexpr int BAR = S1_B + S1_STAGES * 16384;
constexpr int BAR_F1 = BAR, BAR_E1 = BAR + 56, BAR_F2 = BAR + 112, BAR_E2 = BAR + 152, BAR_S1DONE = BAR + 192;
constexpr int DEP_CNT = BAR + 200;
constexpr int SMEM_BYTES = BAR + 256 + 1024;
constexpr int TPITCH = 464;

__device__ __forceinline__ int n_passes(int j) { return j < 4 ? 2 : (j < 6 ? 3 : (j == 6 ? 11 : 10)); }
__device__ __forceinline__ int pass_slab(int j, int p) {
    if (p == 0) return j < 7 ? -1 : 0;
    if (p == 1) return 1 + j;
    if (p == 2) return 5 + j;
    return 13 + 2 * (p - 3) + (j - 6);
}

template <int TB>
__device__ __forceinline__ void s1_mainloop(float (&acc)[2][64], uint32_t sb, int idx, int lane, int handoff) {
    int st = idx % S1_STAGES;
    uint32_t ph = (idx / S1_STAGES) & 1;
    int prev = 0;
    uint64_t da = mkdesc(sb + S1_XN, 16, 1024);
    const uint64_t db0 = TB ? mkdesc(sb + S1_B, 8192, 1024) : mkdesc(sb + S1_B, 16, 1024);
#pragma unroll 1
    for (int kb = 0; kb < 7; kb++) {
        mbar_wait(sb + BAR_F1 + 8 * st, ph);
        if (kb == 6 && handoff) asm volatile("bar.arrive %0, 256;" ::"r"(handoff) : "memory");
        const uint64_t db = db0 + st * 1024;
        wg_arrive();
#pragma unroll
        for (int s = 0; s < 4; s++) {
            wgmma_n128<TB>(acc[0], da + s * 2, db + s * (TB ? 128 : 2), kb | s);
            wgmma_n128<TB>(acc[1], da + 512 + s * 2, db + s * (TB ? 128 : 2), kb | s);
        }
        wg_commit();
        wg_wait<1>();
        if (kb > 0 && lane == 0) mbar_arrive_both(sb + BAR_E1 + 8 * prev);
        prev = st;
        da += 1024;
        if (++st == S1_STAGES) { st = 0; ph ^= 1; }
    }
    wg_wait<0>();
    if (lane == 0) mbar_arrive_both(sb + BAR_E1 + 8 * prev);
}

template <int TB>
__device__ __forceinline__ void s2_mainloop(float (&acc)[112], uint32_t sb, int wg, int lane) {
    constexpr int NST = TB ? F_STAGES : Y_STAGES, SSZ = TB ? F_STAGE : Y_STAGE, NKB = TB ? 28 : 32;
    int st = 0;
    uint32_t ph = 0;
    int prev = 0;
    const uint64_t da0 = mkdesc(sb + wg * 8192, 16, 1024);
    const uint64_t db0 = TB ? mkdesc(sb + 16384, 8192, 1024) : mkdesc(sb + 16384, 16, 1024);
#pragma unroll 1
    for (int i = 0; i < NKB; i++) {
        mbar_wait(sb + BAR_F2 + 8 * st, ph);
        const uint64_t da = da0 + st * (SSZ / 16), db = db0 + st * (SSZ / 16);
        wg_arrive();
#pragma unroll
        for (int s = 0; s < 4; s++) wgmma_n224<TB>(acc, da + s * 2, db + s * (TB ? 128 : 2), i | s);
        wg_commit();
        wg_wait<1>();
        if (i > 0 && lane == 0) mbar_arrive_both(sb + BAR_E2 + 8 * prev);
        prev = st;
        if (++st == NST) { st = 0; ph ^= 1; }
    }
    wg_wait<0>();
}

struct Maps {
    CUtensorMap wg, wu, hre, him, h, abT, sre, sim, wd;
};
struct Ptrs {
    const __nv_bfloat16 *x, *hre, *him, *wg, *wu, *wd;
    __nv_bfloat16* out;
};
__device__ __forceinline__ void mbar_arrive(uint32_t b) {
    asm volatile("mbarrier.arrive.shared::cta.b64 _, [%0];" ::"r"(b) : "memory");
}
__device__ __forceinline__ void l2_prefetch(const void* p, uint32_t bytes) {
    asm volatile("cp.async.bulk.prefetch.L2.global [%0], %1;" ::"l"(p), "r"(bytes) : "memory");
}
__device__ __forceinline__ void tma_prefetch(const CUtensorMap* m, int c0, int c1) {
    asm volatile("cp.async.bulk.prefetch.tensor.2d.L2.global.tile [%0, {%1, %2}];" ::"l"(m), "r"(c0), "r"(c1) : "memory");
}

__device__ __forceinline__ void dep_wait(uint32_t sb, uint32_t need) {
    uint32_t v;
    do { asm volatile("ld.acquire.cta.shared.u32 %0, [%1];" : "=r"(v) : "r"(sb + DEP_CNT) : "memory"); } while (v < need);
}

__global__ void __launch_bounds__(384, 1)
fused_kernel(const __grid_constant__ Ptrs pt, const __grid_constant__ Maps tm) {
    extern __shared__ unsigned char smem_raw[];
    const uint32_t sb = (s2u(smem_raw) + 1023) & ~1023u;
    const int tid = threadIdx.x, lane = tid & 31;
    const int warp = __shfl_sync(0xffffffffu, tid >> 5, 0);
    const int rank = blockIdx.x & 1;
    const int cid = blockIdx.x >> 1;
    const int j = cid & 7;
    const int rb = (cid >> 3) * 2 + rank;
    const int npass = n_passes(j);
    const int n = j & 1;
    const int part = j >> 1;

    {
        const int l8 = lane & 7, sub = lane >> 3;
        uint4 v[3][7];
#pragma unroll
        for (int it = 0; it < 3; it++) {
            const int qd = warp + 12 * it;
            if (qd < 32) {
                const uint4* src = reinterpret_cast<const uint4*>(pt.x + (size_t)(rb * 128 + qd * 4 + sub) * D_) + l8;
#pragma unroll
                for (int i = 0; i < 7; i++) v[it][i] = __ldg(src + i * 8);
            }
        }
        if (tid == 256) {
            TL(0, 0);
            for (int i = 0; i < S1_STAGES; i++) { mbar_init(sb + BAR_F1 + 8 * i, 1); mbar_init(sb + BAR_E1 + 8 * i, 8); }
            for (int i = 0; i < Y_STAGES; i++) { mbar_init(sb + BAR_F2 + 8 * i, 1); mbar_init(sb + BAR_E2 + 8 * i, 16); }
            mbar_init(sb + BAR_S1DONE, 16);
            asm volatile("st.shared.u32 [%0], %1;" ::"r"(sb + DEP_CNT), "r"(0) : "memory");
            asm volatile("fence.mbarrier_init.release.cluster;" ::: "memory");
        }
        __syncwarp();
        asm volatile("barrier.cluster.arrive.relaxed.aligned;\nbarrier.cluster.wait.aligned;" ::: "memory");
        if (tid == 256) {
            const int slab = pass_slab(j, 0);
            for (int kb = 0; kb < 7; kb++) {
                const uint32_t dst = sb + S1_B + kb * 16384 + rank * 8192;
                const uint32_t fb = sb + BAR_F1 + 8 * kb;
                mbar_expect(fb, 16384);
                if (slab >= 0) {
                    tma_load_mc(dst, rank ? &tm.wu : &tm.wg, fb, slab * 64, kb * 64);
                } else {
                    const int a = 2 * j + rank;
                    tma_load_mc(dst, a < 7 ? &tm.hre : &tm.him, fb, kb * 64, (a < 7 ? a : a - 7) * 64);
                }
            }
            const int b = blockIdx.x;
            l2_prefetch((const char*)pt.wg + b * 12544, 12544);
            l2_prefetch((const char*)pt.wu + b * 12544, 12544);
            l2_prefetch((const char*)pt.wd + b * 12544, 12544);
        }
        __syncwarp();
        if (tid == 0) TL(0, 1);
#pragma unroll
        for (int it = 0; it < 3; it++) {
            const int qd = warp + 12 * it;
            if (qd < 32) {
                const int row = qd * 4 + sub;
                float s0 = 0.f, s1 = 0.f;
#pragma unroll
                for (int i = 0; i < 7; i++) {
                    s0 += (bf_lo(v[it][i].x) + bf_hi(v[it][i].x)) + (bf_lo(v[it][i].y) + bf_hi(v[it][i].y));
                    s1 += (bf_lo(v[it][i].z) + bf_hi(v[it][i].z)) + (bf_lo(v[it][i].w) + bf_hi(v[it][i].w));
                }
                float s = s0 + s1;
                s += __shfl_xor_sync(0xffffffffu, s, 1);
                s += __shfl_xor_sync(0xffffffffu, s, 2);
                s += __shfl_xor_sync(0xffffffffu, s, 4);
                if (it == 0 && tid == 0) TL(0, 3);
                const float mean = s * (1.0f / D_);
                float q0 = 0.f, q1 = 0.f;
#pragma unroll
                for (int i = 0; i < 7; i++) {
                    const uint32_t w[4] = {v[it][i].x, v[it][i].y, v[it][i].z, v[it][i].w};
#pragma unroll
                    for (int c = 0; c < 4; c++) {
                        const float d0 = bf_lo(w[c]) - mean, d1 = bf_hi(w[c]) - mean;
                        q0 = fmaf(d0, d0, q0);
                        q1 = fmaf(d1, d1, q1);
                    }
                }
                float q = q0 + q1;
                q += __shfl_xor_sync(0xffffffffu, q, 1);
                q += __shfl_xor_sync(0xffffffffu, q, 2);
                q += __shfl_xor_sync(0xffffffffu, q, 4);
                const float var = rbf(q * (1.0f / D_));
                const float den = rbf(sqrtf(rbf(var + 1e-5f)));
                const float rinv = 1.0f / den;
                const float rhi = rbf(rinv);
                const uint32_t m2 = pack_bf16(mean, mean), rhi2 = pack_bf16(rhi, rhi), rlo2 = pack_bf16(rinv - rhi, rinv - rhi);
                const uint32_t dst = sb + S1_XN + row * 128 + ((l8 ^ (row & 7)) << 4);
#pragma unroll
                for (int i = 0; i < 7; i++) {
                    const uint32_t w[4] = {v[it][i].x, v[it][i].y, v[it][i].z, v[it][i].w};
                    uint32_t o[4];
#pragma unroll
                    for (int c = 0; c < 4; c++) {
                        const uint32_t xc = hsub2(w[c], m2);
                        o[c] = hfma2(xc, rhi2, hmul2(xc, rlo2));
                    }
                    asm volatile("st.shared.v4.b32 [%0], {%1, %2, %3, %4};" ::"r"(dst + i * 16384), "r"(o[0]), "r"(o[1]), "r"(o[2]), "r"(o[3]) : "memory");
                }
            }
        }
        fence_async();
        __syncthreads();
        if (tid == 0) TL(0, 2);
    }

    if (warp >= 8) {
        asm volatile("setmaxnreg.dec.sync.aligned.u32 40;");
        if (warp == 8) {
            if (lane == 0) {
                int st = 0;
                uint32_t ph = 0;
                for (int p = 1; p < npass; p++) {
                    const int slab = pass_slab(j, p);
                    for (int kb = 0; kb < 7; kb++) {
                        mbar_wait(sb + BAR_E1 + 8 * st, ph);
                        const uint32_t fb = sb + BAR_F1 + 8 * st;
                        mbar_expect(fb, 16384);
                        tma_load_mc(sb + S1_B + st * 16384 + rank * 8192, rank ? &tm.wu : &tm.wg, fb, slab * 64, kb * 64);
                        if (++st == S1_STAGES) { st = 0; ph ^= 1; }
                    }
                }
                if (part < 3) {
                    mbar_wait(sb + BAR_S1DONE, 0);
                    TL(0, 24);
                    st = 0; ph = 1;
                    if (part < 2) {
                        const CUtensorMap* ma = part ? &tm.sim : &tm.sre;
                        for (int g = 0; g < 32; g++) {
                            mbar_wait(sb + BAR_E2 + 8 * st, ph);
                            const uint32_t dst = sb + st * Y_STAGE;
                            const uint32_t fb = sb + BAR_F2 + 8 * st;
                            mbar_expect(fb, Y_STAGE);
                            tma_load(dst, ma, fb, g * 64, rb * 128);
                            dep_wait(sb, (g >> 1) + 1);
                            tma_load_mc(dst + 16384 + rank * 14336, &tm.abT, fb, g * 64, part * 448 + n * 224 + rank * 112);
                            if (++st == Y_STAGES) { st = 0; ph ^= 1; }
                        }
                    } else {
                        for (int g = 0; g < 28; g++) {
                            mbar_wait(sb + BAR_E2 + 8 * st, ph);
                            const uint32_t dst = sb + st * F_STAGE;
                            const uint32_t fb = sb + BAR_F2 + 8 * st;
                            mbar_expect(fb, F_STAGE);
                            tma_load_mc(dst + 16384 + (2 * rank) * 8192, &tm.wd, fb, n * 224 + (2 * rank) * 64, g * 64);
                            tma_load_mc(dst + 16384 + (2 * rank + 1) * 8192, &tm.wd, fb, n * 224 + (2 * rank + 1) * 64, g * 64);
                            dep_wait(sb, g + 1);
                            tma_load(dst, &tm.h, fb, g * 64, rb * 128);
                            if (++st == F_STAGES) { st = 0; ph ^= 1; }
                        }
                    }
                }
            }
        } else if (warp == 9) {
            if (lane == 0 && part < 3) {
                if (part < 2) {
                    const CUtensorMap* ma = part ? &tm.sim : &tm.sre;
                    for (int q = 0; q < 16; q++) tma_prefetch(ma, (2 * q + n) * 64, rb * 128);
                }
                const int ndep = part < 2 ? 16 : 28;
                const unsigned int* f = part < 2 ? g_fl.ab : g_fl.h + rb * 28;
                const unsigned int target = part < 2 ? 7 * 4 : 4;
                for (int d = 0; d < ndep; d++) {
                    flag_wait(f + d, target);
                    fence_async_all();
                    asm volatile("st.release.cta.shared.u32 [%0], %1;" ::"r"(sb + DEP_CNT), "r"(d + 1) : "memory");
                }
            }
        }
        __syncwarp();
    } else {
        asm volatile("setmaxnreg.inc.sync.aligned.u32 232;");
        const int wg = warp >> 2, wl = warp & 3, wtid = tid & 127;
        const int qd = lane & 3;
        {
            float acc[2][64];
            for (int p = wg; p < npass; p += 2) {
                const int slab = pass_slab(j, p);
                if (p > 0) bar_sync(4 + (p & 1), 256);
                const int handoff = (p + 1 < npass) ? 4 + ((p + 1) & 1) : 0;
                if (slab >= 0) s1_mainloop<1>(acc, sb, p * 7, lane, handoff);
                else s1_mainloop<0>(acc, sb, p * 7, lane, handoff);
                if (p + 2 >= npass && lane == 0) mbar_arrive_both(sb + BAR_S1DONE);
                if (wtid == 0 && p < 4) TL(0, 4 + p);

                if (slab >= 0) {
                    __nv_bfloat16* dst = g_h + (size_t)(rb * 128 + wl * 16 + (lane >> 2)) * F_ + slab * 64 + qd * 8;
#pragma unroll
                    for (int mh = 0; mh < 2; mh++) {
#pragma unroll
                        for (int hh = 0; hh < 2; hh++) {
#pragma unroll
                            for (int g4 = 0; g4 < 2; g4++) {
                                uint32_t r[4];
#pragma unroll
                                for (int t = 0; t < 4; t++) {
                                    const int o = (g4 * 4 + t) * 4 + hh * 2;
                                    const uint32_t g2 = pack_bf16(acc[mh][o], acc[mh][o + 1]);
                                    const uint32_t u2 = pack_bf16(acc[mh][32 + o], acc[mh][32 + o + 1]);
                                    const uint32_t a2 = pack_bf16(gelu_tanh(bf_lo(g2)), gelu_tanh(bf_hi(g2)));
                                    r[t] = hmul2(a2, u2);
                                }
                                quad_transpose(r, qd);
                                __stcg(reinterpret_cast<uint4*>(dst + (size_t)(mh * 64 + hh * 8) * F_ + g4 * 32), make_uint4(r[0], r[1], r[2], r[3]));
                            }
                        }
                    }
                    __threadfence();
                    __syncwarp();
                    if (lane == 0) flag_add(&g_fl.h[rb * 28 + slab]);
                } else {
                    __nv_bfloat16* dst = g_abT + (size_t)(j * 128 + (qd >> 1) * 8 + (lane >> 2)) * S_ + rb * 128 + wl * 16 + (qd & 1) * 8;
#pragma unroll
                    for (int mh = 0; mh < 2; mh++) {
#pragma unroll
                        for (int jj = 0; jj < 16; jj += 2) {
                            uint32_t r[4];
#pragma unroll
                            for (int t = 0; t < 4; t++) {
                                const int o = (jj + (t >> 1)) * 4 + (t & 1) * 2;
                                r[t] = movmat_t(pack_bf16(acc[mh][o], acc[mh][o + 1]));
                            }
                            quad_transpose(r, qd);
                            __stcg(reinterpret_cast<uint4*>(dst + (size_t)(jj * 8) * S_ + mh * 64), make_uint4(r[0], r[1], r[2], r[3]));
                        }
                    }
                    __threadfence();
                    __syncwarp();
                    if (lane == 0) flag_add(&g_fl.ab[rb]);
                }
                if (wtid == 0 && p < 4) TL(0, 10 + p);
            }
        }
        if (wtid == 0) TL(0, 20 + wg);
        if (part < 3) {
            {
                float acc[112];
                if (part < 2) s2_mainloop<0>(acc, sb, wg, lane);
                else s2_mainloop<1>(acc, sb, wg, lane);
                if (tid == 0) TL(0, 25);
                if (part < 2) {
                    __nv_bfloat16* dst = g_y + (size_t)(part * S_ + rb * 128 + wg * 64 + wl * 16 + (lane >> 2)) * D_ + n * 224 + qd * 8;
#pragma unroll
                    for (int hh = 0; hh < 2; hh++) {
#pragma unroll
                        for (int g4 = 0; g4 < 7; g4++) {
                            uint32_t r[4];
#pragma unroll
                            for (int t = 0; t < 4; t++) r[t] = pack_bf16(acc[(g4 * 4 + t) * 4 + hh * 2], acc[(g4 * 4 + t) * 4 + hh * 2 + 1]);
                            quad_transpose(r, qd);
                            __stcg(reinterpret_cast<uint4*>(dst + (size_t)(hh * 8) * D_ + g4 * 32), make_uint4(r[0], r[1], r[2], r[3]));
                        }
                    }
                    __threadfence();
                    __syncwarp();
                    if (lane == 0) flag_add(&g_fl.y[rb * 2 + n]);
                } else {
                    const size_t base = (size_t)(rb * 128 + wg * 64 + wl * 16 + (lane >> 2)) * D_ + n * 224 + qd * 8;
                    uint4 gv[14];
#pragma unroll
                    for (int hh = 0; hh < 2; hh++) {
#pragma unroll
                        for (int g4 = 0; g4 < 7; g4++) {
                            uint32_t r[4];
#pragma unroll
                            for (int t = 0; t < 4; t++) {
                                const uint32_t f2 = pack_bf16(acc[(g4 * 4 + t) * 4 + hh * 2], acc[(g4 * 4 + t) * 4 + hh * 2 + 1]);
                                r[t] = pack_bf16(silu(bf_lo(f2)), silu(bf_hi(f2)));
                            }
                            quad_transpose(r, qd);
                            gv[hh * 7 + g4] = make_uint4(r[0], r[1], r[2], r[3]);
                        }
                    }
                    uint4 xv[14];
#pragma unroll
                    for (int i = 0; i < 14; i++)
                        xv[i] = __ldg(reinterpret_cast<const uint4*>(pt.x + base + (i / 7) * 8 * D_ + (i % 7) * 32));
                    if (lane == 0) flag_wait(&g_fl.y[rb * 2 + n], 16);
                    __syncwarp();
                    if (tid == 0) TL(0, 26);
#pragma unroll
                    for (int hf = 0; hf < 2; hf++) {
                        uint4 yr[7], yi[7];
#pragma unroll
                        for (int i = 0; i < 7; i++) {
                            yr[i] = __ldcg(reinterpret_cast<const uint4*>(g_y + base + hf * 8 * D_ + i * 32));
                            yi[i] = __ldcg(reinterpret_cast<const uint4*>(g_y + (size_t)S_ * D_ + base + hf * 8 * D_ + i * 32));
                        }
#pragma unroll
                        for (int i = 0; i < 7; i++) {
                            const uint4 g = gv[hf * 7 + i], xx = xv[hf * 7 + i];
                            uint4 o;
                            o.x = hadd2(xx.x, hmul2(hsub2(yr[i].x, yi[i].x), g.x));
                            o.y = hadd2(xx.y, hmul2(hsub2(yr[i].y, yi[i].y), g.y));
                            o.z = hadd2(xx.z, hmul2(hsub2(yr[i].z, yi[i].z), g.z));
                            o.w = hadd2(xx.w, hmul2(hsub2(yr[i].w, yi[i].w), g.w));
                            *reinterpret_cast<uint4*>(pt.out + base + hf * 8 * D_ + i * 32) = o;
                        }
                    }
                }
            }
        }
    }
    if (tid == 0) TL(0, 29);
    cluster_sync();
    if (tid == 0) {
        TL(0, 30);
        __threadfence();
        if (atomicAdd(&g_fl.done, 1u) == gridDim.x - 1) {
            unsigned int* f = reinterpret_cast<unsigned int*>(&g_fl);
            for (int i = 0; i < (int)(sizeof(Flags) / 4); i++) f[i] = 0;
        }
    }
}

typedef CUresult (*EncFn)(CUtensorMap*, CUtensorMapDataType, cuuint32_t, void*, const cuuint64_t*, const cuuint64_t*,
                          const cuuint32_t*, const cuuint32_t*, CUtensorMapInterleave, CUtensorMapSwizzle,
                          CUtensorMapL2promotion, CUtensorMapFloatOOBfill);

void make_map(EncFn enc, CUtensorMap* m, const void* ptr, int rows, int cols, int box_rows, int box_cols, bool swz = true) {
    cuuint64_t gd[2] = {(cuuint64_t)cols, (cuuint64_t)rows};
    cuuint64_t gs[1] = {(cuuint64_t)cols * 2};
    cuuint32_t bx[2] = {(cuuint32_t)box_cols, (cuuint32_t)box_rows};
    cuuint32_t es[2] = {1, 1};
    enc(m, CU_TENSOR_MAP_DATA_TYPE_BFLOAT16, 2, const_cast<void*>(ptr), gd, gs, bx, es, CU_TENSOR_MAP_INTERLEAVE_NONE,
        swz ? CU_TENSOR_MAP_SWIZZLE_128B : CU_TENSOR_MAP_SWIZZLE_NONE, CU_TENSOR_MAP_L2_PROMOTION_L2_128B,
        CU_TENSOR_MAP_FLOAT_OOB_FILL_NONE);
}

}

extern "C" void kernel_launch(void* const* d_in, const int* in_sizes, int n_in, void* d_out, int out_size) {
    Ptrs pt;
    pt.x = (const __nv_bfloat16*)d_in[0];
    pt.hre = (const __nv_bfloat16*)d_in[3];
    pt.him = (const __nv_bfloat16*)d_in[4];
    pt.wg = (const __nv_bfloat16*)d_in[6];
    pt.wu = (const __nv_bfloat16*)d_in[7];
    pt.wd = (const __nv_bfloat16*)d_in[8];
    pt.out = (__nv_bfloat16*)d_out;

    void* fn = nullptr;
    cudaDriverEntryPointQueryResult qr;
    cudaGetDriverEntryPoint("cuTensorMapEncodeTiled", &fn, cudaEnableDefault, &qr);
    EncFn enc = (EncFn)fn;
    void *p_abT, *p_h;
    cudaGetSymbolAddress(&p_abT, g_abT);
    cudaGetSymbolAddress(&p_h, g_h);

    Maps tm;
    make_map(enc, &tm.wg, d_in[6], D_, F_, 64, 64);
    make_map(enc, &tm.wu, d_in[7], D_, F_, 64, 64);
    make_map(enc, &tm.hre, d_in[3], D_, D_, 64, 64);
    make_map(enc, &tm.him, d_in[4], D_, D_, 64, 64);
    make_map(enc, &tm.h, p_h, S_, F_, 128, 64);
    make_map(enc, &tm.abT, p_abT, 896, S_, 112, 64);
    make_map(enc, &tm.sre, d_in[1], S_, S_, 128, 64);
    make_map(enc, &tm.sim, d_in[2], S_, S_, 128, 64);
    make_map(enc, &tm.wd, d_in[8], F_, D_, 64, 64);

    cudaFuncSetAttribute(fused_kernel, cudaFuncAttributeMaxDynamicSharedMemorySize, SMEM_BYTES);

    cudaLaunchAttribute at[1];
    at[0].id = cudaLaunchAttributeClusterDimension;
    at[0].val.clusterDim.x = 2; at[0].val.clusterDim.y = 1; at[0].val.clusterDim.z = 1;
    cudaLaunchConfig_t cfg = {};
    cfg.gridDim = dim3(128); cfg.blockDim = dim3(384); cfg.stream = cudaStreamPerThread;
    cfg.attrs = at; cfg.numAttrs = 1;
    cfg.dynamicSmemBytes = SMEM_BYTES;
    cudaLaunchKernelEx(&cfg, fused_kernel, pt, tm);
}
```

```cpp
#include <cuda_runtime.h>
#include <cuda_bf16.h>
#include <cuda.h>
#include <stdint.h>

namespace {

constexpr int S_ = 2048, D_ = 448, F_ = 1792;

__device__ __align__(1024) __nv_bfloat16 g_abT[896 * 2048];
__device__ __align__(1024) __nv_bfloat16 g_h[2048 * 1792];
__device__ __align__(1024) __nv_bfloat16 g_y[2 * 2048 * 448];
struct Flags {
    unsigned int ab[16];
    unsigned int h[16 * 28];
    unsigned int y[32];
    unsigned int done;
};
__device__ Flags g_fl;

#define TL(k, i) do {} while (0)
__device__ __forceinline__ uint32_t s2u(const void* p) { return (uint32_t)__cvta_generic_to_shared(p); }
__device__ __forceinline__ void mbar_init(uint32_t b, int c) {
    asm volatile("mbarrier.init.shared::cta.b64 [%0], %1;" ::"r"(b), "r"(c));
}
__device__ __forceinline__ void mbar_expect(uint32_t b, uint32_t bytes) {
    asm volatile("mbarrier.arrive.expect_tx.shared::cta.b64 _, [%0], %1;" ::"r"(b), "r"(bytes) : "memory");
}
__device__ __forceinline__ void mbar_wait(uint32_t b, uint32_t ph) {
    uint32_t ok;
    do {
        asm volatile("{\n.reg .pred p;\nmbarrier.try_wait.parity.shared::cta.b64 p, [%1], %2;\nselp.u32 %0, 1, 0, p;\n}"
                     : "=r"(ok) : "r"(b), "r"(ph) : "memory");
    } while (!ok);
}
__device__ __forceinline__ void mbar_arrive_both(uint32_t b) {
    asm volatile("{\n.reg .b32 r0, r1;\n"
                 "mapa.shared::cluster.u32 r0, %0, 0;\n"
                 "mapa.shared::cluster.u32 r1, %0, 1;\n"
                 "mbarrier.arrive.shared::cluster.b64 _, [r0];\n"
                 "mbarrier.arrive.shared::cluster.b64 _, [r1];\n}"
                 ::"r"(b) : "memory");
}
__device__ __forceinline__ void tma_load(uint32_t dst, const CUtensorMap* m, uint32_t bar, int c0, int c1) {
    asm volatile("cp.async.bulk.tensor.2d.shared::cluster.global.mbarrier::complete_tx::bytes [%0], [%1, {%3, %4}], [%2];"
                 ::"r"(dst), "l"(m), "r"(bar), "r"(c0), "r"(c1) : "memory");
}
__device__ __forceinline__ void tma_load_mc(uint32_t dst, const CUtensorMap* m, uint32_t bar, int c0, int c1) {
    asm volatile("cp.async.bulk.tensor.2d.shared::cluster.global.mbarrier::complete_tx::bytes.multicast::cluster [%0], [%1, {%3, %4}], [%2], %5;"
                 ::"r"(dst), "l"(m), "r"(bar), "r"(c0), "r"(c1), "h"((uint16_t)3) : "memory");
}
__device__ __forceinline__ void tma_store(const CUtensorMap* m, uint32_t src, int c0, int c1) {
    asm volatile("cp.async.bulk.tensor.2d.global.shared::cta.bulk_group [%0, {%2, %3}], [%1];"
                 ::"l"(m), "r"(src), "r"(c0), "r"(c1) : "memory");
}
__device__ __forceinline__ void bulk_commit() { asm volatile("cp.async.bulk.commit_group;" ::: "memory"); }
__device__ __forceinline__ void bulk_wait_read0() { asm volatile("cp.async.bulk.wait_group.read 0;" ::: "memory"); }
__device__ __forceinline__ void bulk_wait0() { asm volatile("cp.async.bulk.wait_group 0;" ::: "memory"); }
__device__ __forceinline__ void fence_async() { asm volatile("fence.proxy.async.shared::cta;" ::: "memory"); }
__device__ __forceinline__ void fence_async_all() { asm volatile("fence.proxy.async;" ::: "memory"); }
__device__ __forceinline__ void cluster_sync() {
    asm volatile("barrier.cluster.arrive.release.aligned;\nbarrier.cluster.wait.acquire.aligned;" ::: "memory");
}
__device__ __forceinline__ void bar_sync(int id, int n) { asm volatile("bar.sync %0, %1;" ::"r"(id), "r"(n) : "memory"); }
__device__ __forceinline__ void wg_arrive() { asm volatile("wgmma.fence.sync.aligned;" ::: "memory"); }
__device__ __forceinline__ void wg_commit() { asm volatile("wgmma.commit_group.sync.aligned;" ::: "memory"); }
template <int N> __device__ __forceinline__ void wg_wait() { asm volatile("wgmma.wait_group.sync.aligned %0;" ::"n"(N) : "memory"); }
__device__ __forceinline__ void stmat4(uint32_t a, uint32_t r0, uint32_t r1, uint32_t r2, uint32_t r3) {
    asm volatile("stmatrix.sync.aligned.m8n8.x4.shared.b16 [%0], {%1, %2, %3, %4};" ::"r"(a), "r"(r0), "r"(r1), "r"(r2), "r"(r3) : "memory");
}
__device__ __forceinline__ void stmat4t(uint32_t a, uint32_t r0, uint32_t r1, uint32_t r2, uint32_t r3) {
    asm volatile("stmatrix.sync.aligned.m8n8.x4.trans.shared.b16 [%0], {%1, %2, %3, %4};" ::"r"(a), "r"(r0), "r"(r1), "r"(r2), "r"(r3) : "memory");
}
__device__ __forceinline__ void ldmat4(uint32_t a, uint32_t (&r)[4]) {
    asm volatile("ldmatrix.sync.aligned.m8n8.x4.shared.b16 {%0, %1, %2, %3}, [%4];"
                 : "=r"(r[0]), "=r"(r[1]), "=r"(r[2]), "=r"(r[3]) : "r"(a) : "memory");
}
__device__ __forceinline__ void flag_add(unsigned int* f) {
    asm volatile("red.release.gpu.global.add.u32 [%0], 1;" ::"l"(f) : "memory");
}
__device__ __forceinline__ void flag_wait(const unsigned int* f, unsigned int target) {
    unsigned int v;
    int spins = 0;
    while (true) {
        asm volatile("ld.acquire.gpu.global.u32 %0, [%1];" : "=r"(v) : "l"(f) : "memory");
        if (v >= target || ++spins > (1 << 22)) break;
    }
}
__device__ __forceinline__ void quad_transpose(uint32_t (&r)[4], int q) {
    const bool o1 = q & 1, o2 = q & 2;
    uint32_t a = o1 ? r[0] : r[1], b = o1 ? r[2] : r[3];
    a = __shfl_xor_sync(0xffffffffu, a, 1);
    b = __shfl_xor_sync(0xffffffffu, b, 1);
    if (o1) { r[0] = a; r[2] = b; } else { r[1] = a; r[3] = b; }
    a = o2 ? r[0] : r[2]; b = o2 ? r[1] : r[3];
    a = __shfl_xor_sync(0xffffffffu, a, 2);
    b = __shfl_xor_sync(0xffffffffu, b, 2);
    if (o2) { r[0] = a; r[1] = b; } else { r[2] = a; r[3] = b; }
}
__device__ __forceinline__ uint32_t movmat_t(uint32_t v) {
    uint32_t r;
    asm volatile("movmatrix.sync.aligned.m8n8.trans.b16 %0, %1;" : "=r"(r) : "r"(v));
    return r;
}
__device__ __forceinline__ uint64_t mkdesc(uint32_t addr, uint32_t lbo, uint32_t sbo) {
    return (uint64_t)((addr & 0x3FFFF) >> 4) | ((uint64_t)(lbo >> 4) << 16) | ((uint64_t)(sbo >> 4) << 32) | (1ull << 62);
}
__device__ __forceinline__ uint32_t pack_bf16(float lo, float hi) {
    uint32_t r;
    asm("cvt.rn.bf16x2.f32 %0, %1, %2;" : "=r"(r) : "f"(hi), "f"(lo));
    return r;
}
__device__ __forceinline__ uint32_t hsub2(uint32_t a, uint32_t b) { uint32_t r; asm("sub.rn.bf16x2 %0, %1, %2;" : "=r"(r) : "r"(a), "r"(b)); return r; }
__device__ __forceinline__ uint32_t hadd2(uint32_t a, uint32_t b) { uint32_t r; asm("add.rn.bf16x2 %0, %1, %2;" : "=r"(r) : "r"(a), "r"(b)); return r; }
__device__ __forceinline__ uint32_t hmul2(uint32_t a, uint32_t b) { uint32_t r; asm("mul.rn.bf16x2 %0, %1, %2;" : "=r"(r) : "r"(a), "r"(b)); return r; }
__device__ __forceinline__ uint32_t hfma2(uint32_t a, uint32_t b, uint32_t c) { uint32_t r; asm("fma.rn.bf16x2 %0, %1, %2, %3;" : "=r"(r) : "r"(a), "r"(b), "r"(c)); return r; }
__device__ __forceinline__ float bf_lo(uint32_t u) { return __uint_as_float(u << 16); }
__device__ __forceinline__ float bf_hi(uint32_t u) { return __uint_as_float(u & 0xffff0000u); }
__device__ __forceinline__ float rbf(float v) { return __bfloat162float(__float2bfloat16_rn(v)); }
__device__ __forceinline__ float tanh_fast(float x) { float r; asm("tanh.approx.f32 %0, %1;" : "=f"(r) : "f"(x)); return r; }
__device__ __forceinline__ float gelu_tanh(float x) {
    float u = x * fmaf(x * x, 0.0356774081f, 0.7978845608f);
    float hx = 0.5f * x;
    return fmaf(hx, tanh_fast(u), hx);
}
__device__ __forceinline__ float silu(float f) { const float hf = 0.5f * f; return fmaf(hf, tanh_fast(hf), hf); }

template <int TB>
__device__ __forceinline__ void wgmma_n128(float (&d)[64], uint64_t da, uint64_t db, int scaleD) {
    asm volatile("{\n.reg .pred p;\nsetp.ne.b32 p, %66, 0;\n"
        "wgmma.mma_async.sync.aligned.m64n128k16.f32.bf16.bf16 {%0, %1, %2, %3, %4, %5, %6, %7, %8, %9, %10, %11, %12, %13, %14, %15, %16, %17, %18, %19, %20, %21, %22, %23, %24, %25, %26, %27, %28, %29, %30, %31, %32, %33, %34, %35, %36, %37, %38, %39, %40, %41, %42, %43, %44, %45, %46, %47, %48, %49, %50, %51, %52, %53, %54, %55, %56, %57, %58, %59, %60, %61, %62, %63}, %64, %65, p, 1, 1, 0, %67;\n}\n"
        : "+f"(d[0]), "+f"(d[1]), "+f"(d[2]), "+f"(d[3]), "+f"(d[4]), "+f"(d[5]), "+f"(d[6]), "+f"(d[7]), "+f"(d[8]), "+f"(d[9]), "+f"(d[10]), "+f"(d[11]), "+f"(d[12]), "+f"(d[13]), "+f"(d[14]), "+f"(d[15]), "+f"(d[16]), "+f"(d[17]), "+f"(d[18]), "+f"(d[19]), "+f"(d[20]), "+f"(d[21]), "+f"(d[22]), "+f"(d[23]), "+f"(d[24]), "+f"(d[25]), "+f"(d[26]), "+f"(d[27]), "+f"(d[28]), "+f"(d[29]), "+f"(d[30]), "+f"(d[31]), "+f"(d[32]), "+f"(d[33]), "+f"(d[34]), "+f"(d[35]), "+f"(d[36]), "+f"(d[37]), "+f"(d[38]), "+f"(d[39]), "+f"(d[40]), "+f"(d[41]), "+f"(d[42]), "+f"(d[43]), "+f"(d[44]), "+f"(d[45]), "+f"(d[46]), "+f"(d[47]), "+f"(d[48]), "+f"(d[49]), "+f"(d[50]), "+f"(d[51]), "+f"(d[52]), "+f"(d[53]), "+f"(d[54]), "+f"(d[55]), "+f"(d[56]), "+f"(d[57]), "+f"(d[58]), "+f"(d[59]), "+f"(d[60]), "+f"(d[61]), "+f"(d[62]), "+f"(d[63])
        : "l"(da), "l"(db), "r"(scaleD), "n"(TB));
}
template <int TB>
__device__ __forceinline__ void wgmma_n224(float (&d)[112], uint64_t da, uint64_t db, int scaleD) {
    asm volatile("{\n.reg .pred p;\nsetp.ne.b32 p, %114, 0;\n"
        "wgmma.mma_async.sync.aligned.m64n224k16.f32.bf16.bf16 {%0, %1, %2, %3, %4, %5, %6, %7, %8, %9, %10, %11, %12, %13, %14, %15, %16, %17, %18, %19, %20, %21, %22, %23, %24, %25, %26, %27, %28, %29, %30, %31, %32, %33, %34, %35, %36, %37, %38, %39, %40, %41, %42, %43, %44, %45, %46, %47, %48, %49, %50, %51, %52, %53, %54, %55, %56, %57, %58, %59, %60, %61, %62, %63, %64, %65, %66, %67, %68, %69, %70, %71, %72, %73, %74, %75, %76, %77, %78, %79, %80, %81, %82, %83, %84, %85, %86, %87, %88, %89, %90, %91, %92, %93, %94, %95, %96, %97, %98, %99, %100, %101, %102, %103, %104, %105, %106, %107, %108, %109, %110, %111}, %112, %113, p, 1, 1, 0, %115;\n}\n"
        : "+f"(d[0]), "+f"(d[1]), "+f"(d[2]), "+f"(d[3]), "+f"(d[4]), "+f"(d[5]), "+f"(d[6]), "+f"(d[7]), "+f"(d[8]), "+f"(d[9]), "+f"(d[10]), "+f"(d[11]), "+f"(d[12]), "+f"(d[13]), "+f"(d[14]), "+f"(d[15]), "+f"(d[16]), "+f"(d[17]), "+f"(d[18]), "+f"(d[19]), "+f"(d[20]), "+f"(d[21]), "+f"(d[22]), "+f"(d[23]), "+f"(d[24]), "+f"(d[25]), "+f"(d[26]), "+f"(d[27]), "+f"(d[28]), "+f"(d[29]), "+f"(d[30]), "+f"(d[31]), "+f"(d[32]), "+f"(d[33]), "+f"(d[34]), "+f"(d[35]), "+f"(d[36]), "+f"(d[37]), "+f"(d[38]), "+f"(d[39]), "+f"(d[40]), "+f"(d[41]), "+f"(d[42]), "+f"(d[43]), "+f"(d[44]), "+f"(d[45]), "+f"(d[46]), "+f"(d[47]), "+f"(d[48]), "+f"(d[49]), "+f"(d[50]), "+f"(d[51]), "+f"(d[52]), "+f"(d[53]), "+f"(d[54]), "+f"(d[55]), "+f"(d[56]), "+f"(d[57]), "+f"(d[58]), "+f"(d[59]), "+f"(d[60]), "+f"(d[61]), "+f"(d[62]), "+f"(d[63]), "+f"(d[64]), "+f"(d[65]), "+f"(d[66]), "+f"(d[67]), "+f"(d[68]), "+f"(d[69]), "+f"(d[70]), "+f"(d[71]), "+f"(d[72]), "+f"(d[73]), "+f"(d[74]), "+f"(d[75]), "+f"(d[76]), "+f"(d[77]), "+f"(d[78]), "+f"(d[79]), "+f"(d[80]), "+f"(d[81]), "+f"(d[82]), "+f"(d[83]), "+f"(d[84]), "+f"(d[85]), "+f"(d[86]), "+f"(d[87]), "+f"(d[88]), "+f"(d[89]), "+f"(d[90]), "+f"(d[91]), "+f"(d[92]), "+f"(d[93]), "+f"(d[94]), "+f"(d[95]), "+f"(d[96]), "+f"(d[97]), "+f"(d[98]), "+f"(d[99]), "+f"(d[100]), "+f"(d[101]), "+f"(d[102]), "+f"(d[103]), "+f"(d[104]), "+f"(d[105]), "+f"(d[106]), "+f"(d[107]), "+f"(d[108]), "+f"(d[109]), "+f"(d[110]), "+f"(d[111])
        : "l"(da), "l"(db), "r"(scaleD), "n"(TB));
}

constexpr int S1_STAGES = 7;
constexpr int S1_XN = 0;
constexpr int S1_B = 7 * 16384;
constexpr int Y_STAGES = 5, Y_STAGE = 45056;
constexpr int F_STAGES = 4, F_STAGE = 49152;
constexpr int BAR = S1_B + S1_STAGES * 16384;
constexpr int BAR_F1 = BAR, BAR_E1 = BAR + 56, BAR_F2 = BAR + 112, BAR_E2 = BAR + 152, BAR_S1DONE = BAR + 192;
constexpr int BAR_PUB = BAR + 208;
constexpr int DEP_CNT = BAR + 200;
constexpr int SMEM_BYTES = BAR + 256 + 1024;
constexpr int TPITCH = 464;

__device__ __forceinline__ int n_passes(int j) { return j < 4 ? 2 : (j < 6 ? 3 : (j == 6 ? 11 : 10)); }
__device__ __forceinline__ int pass_slab(int j, int p) {
    if (p == 0) return j < 7 ? -1 : 0;
    if (p == 1) return 1 + j;
    if (p == 2) return 5 + j;
    return 13 + 2 * (p - 3) + (j - 6);
}

template <int TB>
__device__ __forceinline__ void s1_mainloop(float (&acc)[2][64], uint32_t sb, int idx, int lane, int handoff) {
    int st = idx % S1_STAGES;
    uint32_t ph = (idx / S1_STAGES) & 1;
    int prev = 0;
    uint64_t da = mkdesc(sb + S1_XN, 16, 1024);
    const uint64_t db0 = TB ? mkdesc(sb + S1_B, 8192, 1024) : mkdesc(sb + S1_B, 16, 1024);
#pragma unroll 1
    for (int kb = 0; kb < 7; kb++) {
        mbar_wait(sb + BAR_F1 + 8 * st, ph);
        if (kb == 6 && handoff) asm volatile("bar.arrive %0, 256;" ::"r"(handoff) : "memory");
        const uint64_t db = db0 + st * 1024;
        wg_arrive();
#pragma unroll
        for (int s = 0; s < 4; s++) {
            wgmma_n128<TB>(acc[0], da + s * 2, db + s * (TB ? 128 : 2), kb | s);
            wgmma_n128<TB>(acc[1], da + 512 + s * 2, db + s * (TB ? 128 : 2), kb | s);
        }
        wg_commit();
        wg_wait<1>();
        if (kb > 0 && lane == 0) mbar_arrive_both(sb + BAR_E1 + 8 * prev);
        prev = st;
        da += 1024;
        if (++st == S1_STAGES) { st = 0; ph ^= 1; }
    }
    wg_wait<0>();
    if (lane == 0) mbar_arrive_both(sb + BAR_E1 + 8 * prev);
}

template <int TB>
__device__ __forceinline__ void s2_mainloop(float (&acc)[112], uint32_t sb, int wg, int lane) {
    constexpr int NST = TB ? F_STAGES : Y_STAGES, SSZ = TB ? F_STAGE : Y_STAGE, NKB = TB ? 28 : 32;
    int st = 0;
    uint32_t ph = 0;
    int prev = 0;
    const uint64_t da0 = mkdesc(sb + wg * 8192, 16, 1024);
    const uint64_t db0 = TB ? mkdesc(sb + 16384, 8192, 1024) : mkdesc(sb + 16384, 16, 1024);
#pragma unroll 1
    for (int i = 0; i < NKB; i++) {
        mbar_wait(sb + BAR_F2 + 8 * st, ph);
        const uint64_t da = da0 + st * (SSZ / 16), db = db0 + st * (SSZ / 16);
        wg_arrive();
#pragma unroll
        for (int s = 0; s < 4; s++) wgmma_n224<TB>(acc, da + s * 2, db + s * (TB ? 128 : 2), i | s);
        wg_commit();
        wg_wait<1>();
        if (i > 0 && lane == 0) mbar_arrive_both(sb + BAR_E2 + 8 * prev);
        prev = st;
        if (++st == NST) { st = 0; ph ^= 1; }
    }
    wg_wait<0>();
}

struct Maps {
    CUtensorMap wg, wu, hre, him, h, abT, sre, sim, wd;
};
struct Ptrs {
    const __nv_bfloat16 *x, *hre, *him, *wg, *wu, *wd;
    __nv_bfloat16* out;
};
__device__ __forceinline__ void mbar_arrive(uint32_t b) {
    asm volatile("mbarrier.arrive.shared::cta.b64 _, [%0];" ::"r"(b) : "memory");
}
__device__ __forceinline__ void l2_prefetch(const void* p, uint32_t bytes) {
    asm volatile("cp.async.bulk.prefetch.L2.global [%0], %1;" ::"l"(p), "r"(bytes) : "memory");
}
__device__ __forceinline__ void tma_prefetch(const CUtensorMap* m, int c0, int c1) {
    asm volatile("cp.async.bulk.prefetch.tensor.2d.L2.global.tile [%0, {%1, %2}];" ::"l"(m), "r"(c0), "r"(c1) : "memory");
}

__device__ __forceinline__ void dep_wait(uint32_t sb, uint32_t need) {
    uint32_t v;
    do { asm volatile("ld.acquire.cta.shared.u32 %0, [%1];" : "=r"(v) : "r"(sb + DEP_CNT) : "memory"); } while (v < need);
}

__global__ void __launch_bounds__(384, 1)
fused_kernel(const __grid_constant__ Ptrs pt, const __grid_constant__ Maps tm) {
    extern __shared__ unsigned char smem_raw[];
    const uint32_t sb = (s2u(smem_raw) + 1023) & ~1023u;
    const int tid = threadIdx.x, lane = tid & 31;
    const int warp = __shfl_sync(0xffffffffu, tid >> 5, 0);
    const int rank = blockIdx.x & 1;
    const int cid = blockIdx.x >> 1;
    const int j = cid & 7;
    const int rb = (cid >> 3) * 2 + rank;
    const int npass = n_passes(j);
    const int n = j & 1;
    const int part = j >> 1;

    {
        const int l8 = lane & 7, sub = lane >> 3;
        uint4 v[3][7];
#pragma unroll
        for (int it = 0; it < 3; it++) {
            const int qd = warp + 12 * it;
            if (qd < 32) {
                const uint4* src = reinterpret_cast<const uint4*>(pt.x + (size_t)(rb * 128 + qd * 4 + sub) * D_) + l8;
#pragma unroll
                for (int i = 0; i < 7; i++) v[it][i] = __ldg(src + i * 8);
            }
        }
        if (tid == 256) {
            TL(0, 0);
            for (int i = 0; i < S1_STAGES; i++) { mbar_init(sb + BAR_F1 + 8 * i, 1); mbar_init(sb + BAR_E1 + 8 * i, 8); }
            for (int i = 0; i < Y_STAGES; i++) { mbar_init(sb + BAR_F2 + 8 * i, 1); mbar_init(sb + BAR_E2 + 8 * i, 16); }
            mbar_init(sb + BAR_S1DONE, 16);
            mbar_init(sb + BAR_PUB, 4);
            mbar_init(sb + BAR_PUB + 8, 4);
            asm volatile("st.shared.u32 [%0], %1;" ::"r"(sb + DEP_CNT), "r"(0) : "memory");
            asm volatile("fence.mbarrier_init.release.cluster;" ::: "memory");
        }
        __syncwarp();
        asm volatile("barrier.cluster.arrive.relaxed.aligned;\nbarrier.cluster.wait.aligned;" ::: "memory");
        if (tid == 256) {
            const int slab = pass_slab(j, 0);
            for (int kb = 0; kb < 7; kb++) {
                const uint32_t dst = sb + S1_B + kb * 16384 + rank * 8192;
                const uint32_t fb = sb + BAR_F1 + 8 * kb;
                mbar_expect(fb, 16384);
                if (slab >= 0) {
                    tma_load_mc(dst, rank ? &tm.wu : &tm.wg, fb, slab * 64, kb * 64);
                } else {
                    const int a = 2 * j + rank;
                    tma_load_mc(dst, a < 7 ? &tm.hre : &tm.him, fb, kb * 64, (a < 7 ? a : a - 7) * 64);
                }
            }
            const int b = blockIdx.x;
            l2_prefetch((const char*)pt.wg + b * 12544, 12544);
            l2_prefetch((const char*)pt.wu + b * 12544, 12544);
            l2_prefetch((const char*)pt.wd + b * 12544, 12544);
        }
        __syncwarp();
        if (tid == 0) TL(0, 1);
#pragma unroll
        for (int it = 0; it < 3; it++) {
            const int qd = warp + 12 * it;
            if (qd < 32) {
                const int row = qd * 4 + sub;
                float s0 = 0.f, s1 = 0.f;
#pragma unroll
                for (int i = 0; i < 7; i++) {
                    s0 += (bf_lo(v[it][i].x) + bf_hi(v[it][i].x)) + (bf_lo(v[it][i].y) + bf_hi(v[it][i].y));
                    s1 += (bf_lo(v[it][i].z) + bf_hi(v[it][i].z)) + (bf_lo(v[it][i].w) + bf_hi(v[it][i].w));
                }
                float s = s0 + s1;
                s += __shfl_xor_sync(0xffffffffu, s, 1);
                s += __shfl_xor_sync(0xffffffffu, s, 2);
                s += __shfl_xor_sync(0xffffffffu, s, 4);
                if (it == 0 && tid == 0) TL(0, 3);
                const float mean = s * (1.0f / D_);
                float q0 = 0.f, q1 = 0.f;
#pragma unroll
                for (int i = 0; i < 7; i++) {
                    const uint32_t w[4] = {v[it][i].x, v[it][i].y, v[it][i].z, v[it][i].w};
#pragma unroll
                    for (int c = 0; c < 4; c++) {
                        const float d0 = bf_lo(w[c]) - mean, d1 = bf_hi(w[c]) - mean;
                        q0 = fmaf(d0, d0, q0);
                        q1 = fmaf(d1, d1, q1);
                    }
                }
                float q = q0 + q1;
                q += __shfl_xor_sync(0xffffffffu, q, 1);
                q += __shfl_xor_sync(0xffffffffu, q, 2);
                q += __shfl_xor_sync(0xffffffffu, q, 4);
                const float var = rbf(q * (1.0f / D_));
                const float den = rbf(sqrtf(rbf(var + 1e-5f)));
                const float rinv = 1.0f / den;
                const float rhi = rbf(rinv);
                const uint32_t m2 = pack_bf16(mean, mean), rhi2 = pack_bf16(rhi, rhi), rlo2 = pack_bf16(rinv - rhi, rinv - rhi);
                const uint32_t dst = sb + S1_XN + row * 128 + ((l8 ^ (row & 7)) << 4);
#pragma unroll
                for (int i = 0; i < 7; i++) {
                    const uint32_t w[4] = {v[it][i].x, v[it][i].y, v[it][i].z, v[it][i].w};
                    uint32_t o[4];
#pragma unroll
                    for (int c = 0; c < 4; c++) {
                        const uint32_t xc = hsub2(w[c], m2);
                        o[c] = hfma2(xc, rhi2, hmul2(xc, rlo2));
                    }
                    asm volatile("st.shared.v4.b32 [%0], {%1, %2, %3, %4};" ::"r"(dst + i * 16384), "r"(o[0]), "r"(o[1]), "r"(o[2]), "r"(o[3]) : "memory");
                }
            }
        }
        fence_async();
        __syncthreads();
        if (tid == 0) TL(0, 2);
    }

    if (warp >= 8) {
        asm volatile("setmaxnreg.dec.sync.aligned.u32 40;");
        if (warp == 8) {
            if (lane == 0) {
                int st = 0;
                uint32_t ph = 0;
                for (int p = 1; p < npass; p++) {
                    const int slab = pass_slab(j, p);
                    for (int kb = 0; kb < 7; kb++) {
                        mbar_wait(sb + BAR_E1 + 8 * st, ph);
                        const uint32_t fb = sb + BAR_F1 + 8 * st;
                        mbar_expect(fb, 16384);
                        tma_load_mc(sb + S1_B + st * 16384 + rank * 8192, rank ? &tm.wu : &tm.wg, fb, slab * 64, kb * 64);
                        if (++st == S1_STAGES) { st = 0; ph ^= 1; }
                    }
                }
                if (part < 3) {
                    mbar_wait(sb + BAR_S1DONE, 0);
                    TL(0, 24);
                    st = 0; ph = 1;
                    if (part < 2) {
                        const CUtensorMap* ma = part ? &tm.sim : &tm.sre;
                        for (int g = 0; g < 32; g++) {
                            mbar_wait(sb + BAR_E2 + 8 * st, ph);
                            const uint32_t dst = sb + st * Y_STAGE;
                            const uint32_t fb = sb + BAR_F2 + 8 * st;
                            mbar_expect(fb, Y_STAGE);
                            tma_load(dst, ma, fb, g * 64, rb * 128);
                            dep_wait(sb, (g >> 1) + 1);
                            tma_load_mc(dst + 16384 + rank * 14336, &tm.abT, fb, g * 64, part * 448 + n * 224 + rank * 112);
                            if (++st == Y_STAGES) { st = 0; ph ^= 1; }
                        }
                    } else {
                        for (int g = 0; g < 28; g++) {
                            mbar_wait(sb + BAR_E2 + 8 * st, ph);
                            const uint32_t dst = sb + st * F_STAGE;
                            const uint32_t fb = sb + BAR_F2 + 8 * st;
                            mbar_expect(fb, F_STAGE);
                            tma_load_mc(dst + 16384 + (2 * rank) * 8192, &tm.wd, fb, n * 224 + (2 * rank) * 64, g * 64);
                            tma_load_mc(dst + 16384 + (2 * rank + 1) * 8192, &tm.wd, fb, n * 224 + (2 * rank + 1) * 64, g * 64);
                            dep_wait(sb, g + 1);
                            tma_load(dst, &tm.h, fb, g * 64, rb * 128);
                            if (++st == F_STAGES) { st = 0; ph ^= 1; }
                        }
                    }
                }
            }
        } else if (warp == 9) {
            if (lane == 0 && part < 3) {
                if (part < 2) {
                    const CUtensorMap* ma = part ? &tm.sim : &tm.sre;
                    for (int q = 0; q < 16; q++) tma_prefetch(ma, (2 * q + n) * 64, rb * 128);
                }
                const int ndep = part < 2 ? 16 : 28;
                const unsigned int* f = part < 2 ? g_fl.ab : g_fl.h + rb * 28;
                const unsigned int target = part < 2 ? 7 : 1;
                for (int d = 0; d < ndep; d++) {
                    flag_wait(f + d, target);
                    fence_async_all();
                    asm volatile("st.release.cta.shared.u32 [%0], %1;" ::"r"(sb + DEP_CNT), "r"(d + 1) : "memory");
                }
                if (part == 2) {
                    flag_wait(&g_fl.y[rb * 2 + n], 16);
                    asm volatile("st.release.cta.shared.u32 [%0], %1;" ::"r"(sb + DEP_CNT), "r"(29) : "memory");
                }
            }
        } else {
            if (lane == 0) {
                const int w = warp - 10;
                uint32_t ph = 0;
                for (int p = w; p < npass; p += 2) {
                    const int slab = pass_slab(j, p);
                    mbar_wait(sb + BAR_PUB + 8 * w, ph);
                    ph ^= 1;
                    __threadfence();
                    flag_add(slab >= 0 ? &g_fl.h[rb * 28 + slab] : &g_fl.ab[rb]);
                }
            }
        }
        __syncwarp();
    } else {
        asm volatile("setmaxnreg.inc.sync.aligned.u32 232;");
        const int wg = warp >> 2, wl = warp & 3, wtid = tid & 127;
        const int qd = lane & 3;
        {
            float acc[2][64];
            for (int p = wg; p < npass; p += 2) {
                const int slab = pass_slab(j, p);
                if (p > 0) bar_sync(4 + (p & 1), 256);
                const int handoff = (p + 1 < npass) ? 4 + ((p + 1) & 1) : 0;
                if (slab >= 0) s1_mainloop<1>(acc, sb, p * 7, lane, handoff);
                else s1_mainloop<0>(acc, sb, p * 7, lane, handoff);
                if (p + 2 >= npass && lane == 0) mbar_arrive_both(sb + BAR_S1DONE);
                if (wtid == 0 && p < 4) TL(0, 4 + p);

                if (slab >= 0) {
                    __nv_bfloat16* dst = g_h + (size_t)(rb * 128 + wl * 16 + (lane >> 2)) * F_ + slab * 64 + qd * 8;
#pragma unroll
                    for (int mh = 0; mh < 2; mh++) {
#pragma unroll
                        for (int hh = 0; hh < 2; hh++) {
#pragma unroll
                            for (int g4 = 0; g4 < 2; g4++) {
                                uint32_t r[4];
#pragma unroll
                                for (int t = 0; t < 4; t++) {
                                    const int o = (g4 * 4 + t) * 4 + hh * 2;
                                    const uint32_t g2 = pack_bf16(acc[mh][o], acc[mh][o + 1]);
                                    const uint32_t u2 = pack_bf16(acc[mh][32 + o], acc[mh][32 + o + 1]);
                                    const uint32_t a2 = pack_bf16(gelu_tanh(bf_lo(g2)), gelu_tanh(bf_hi(g2)));
                                    r[t] = hmul2(a2, u2);
                                }
                                quad_transpose(r, qd);
                                __stcg(reinterpret_cast<uint4*>(dst + (size_t)(mh * 64 + hh * 8) * F_ + g4 * 32), make_uint4(r[0], r[1], r[2], r[3]));
                            }
                        }
                    }
                } else {
                    __nv_bfloat16* dst = g_abT + (size_t)(j * 128 + (qd >> 1) * 8 + (lane >> 2)) * S_ + rb * 128 + wl * 16 + (qd & 1) * 8;
#pragma unroll
                    for (int mh = 0; mh < 2; mh++) {
#pragma unroll
                        for (int jj = 0; jj < 16; jj += 2) {
                            uint32_t r[4];
#pragma unroll
                            for (int t = 0; t < 4; t++) {
                                const int o = (jj + (t >> 1)) * 4 + (t & 1) * 2;
                                r[t] = movmat_t(pack_bf16(acc[mh][o], acc[mh][o + 1]));
                            }
                            quad_transpose(r, qd);
                            __stcg(reinterpret_cast<uint4*>(dst + (size_t)(jj * 8) * S_ + mh * 64), make_uint4(r[0], r[1], r[2], r[3]));
                        }
                    }
                }
                __syncwarp();
                if (lane == 0) mbar_arrive(sb + BAR_PUB + 8 * wg);
                if (wtid == 0 && p < 4) TL(0, 10 + p);
            }
        }
        if (wtid == 0) TL(0, 20 + wg);
        if (part < 3) {
            {
                float acc[112];
                if (part < 2) s2_mainloop<0>(acc, sb, wg, lane);
                else s2_mainloop<1>(acc, sb, wg, lane);
                if (tid == 0) TL(0, 25);
                if (part < 2) {
                    __nv_bfloat16* dst = g_y + (size_t)(part * S_ + rb * 128 + wg * 64 + wl * 16 + (lane >> 2)) * D_ + n * 224 + qd * 8;
#pragma unroll
                    for (int hh = 0; hh < 2; hh++) {
#pragma unroll
                        for (int g4 = 0; g4 < 7; g4++) {
                            uint32_t r[4];
#pragma unroll
                            for (int t = 0; t < 4; t++) r[t] = pack_bf16(acc[(g4 * 4 + t) * 4 + hh * 2], acc[(g4 * 4 + t) * 4 + hh * 2 + 1]);
                            quad_transpose(r, qd);
                            __stcg(reinterpret_cast<uint4*>(dst + (size_t)(hh * 8) * D_ + g4 * 32), make_uint4(r[0], r[1], r[2], r[3]));
                        }
                    }
                    __threadfence();
                    __syncwarp();
                    if (lane == 0) flag_add(&g_fl.y[rb * 2 + n]);
                } else {
                    const size_t base = (size_t)(rb * 128 + wg * 64 + wl * 16 + (lane >> 2)) * D_ + n * 224 + qd * 8;
                    dep_wait(sb, 29);
                    if (tid == 0) TL(0, 26);
#pragma unroll
                    for (int hh = 0; hh < 2; hh++) {
                        uint4 xv[7], yr[7], yi[7];
#pragma unroll
                        for (int i = 0; i < 7; i++) {
                            yr[i] = __ldcg(reinterpret_cast<const uint4*>(g_y + base + hh * 8 * D_ + i * 32));
                            yi[i] = __ldcg(reinterpret_cast<const uint4*>(g_y + (size_t)S_ * D_ + base + hh * 8 * D_ + i * 32));
                            xv[i] = __ldg(reinterpret_cast<const uint4*>(pt.x + base + hh * 8 * D_ + i * 32));
                        }
#pragma unroll
                        for (int g4 = 0; g4 < 7; g4++) {
                            uint32_t r[4];
#pragma unroll
                            for (int t = 0; t < 4; t++) {
                                const uint32_t f2 = pack_bf16(acc[(g4 * 4 + t) * 4 + hh * 2], acc[(g4 * 4 + t) * 4 + hh * 2 + 1]);
                                r[t] = pack_bf16(silu(bf_lo(f2)), silu(bf_hi(f2)));
                            }
                            quad_transpose(r, qd);
                            uint4 o;
                            o.x = hadd2(xv[g4].x, hmul2(hsub2(yr[g4].x, yi[g4].x), r[0]));
                            o.y = hadd2(xv[g4].y, hmul2(hsub2(yr[g4].y, yi[g4].y), r[1]));
                            o.z = hadd2(xv[g4].z, hmul2(hsub2(yr[g4].z, yi[g4].z), r[2]));
                            o.w = hadd2(xv[g4].w, hmul2(hsub2(yr[g4].w, yi[g4].w), r[3]));
                            *reinterpret_cast<uint4*>(pt.out + base + hh * 8 * D_ + g4 * 32) = o;
                        }
                    }
                }
            }
        }
    }
    if (tid == 0) TL(0, 29);
    cluster_sync();
    if (tid == 0) {
        TL(0, 30);
        __threadfence();
        if (atomicAdd(&g_fl.done, 1u) == gridDim.x - 1) {
            unsigned int* f = reinterpret_cast<unsigned int*>(&g_fl);
            for (int i = 0; i < (int)(sizeof(Flags) / 4); i++) f[i] = 0;
        }
    }
}

typedef CUresult (*EncFn)(CUtensorMap*, CUtensorMapDataType, cuuint32_t, void*, const cuuint64_t*, const cuuint64_t*,
                          const cuuint32_t*, const cuuint32_t*, CUtensorMapInterleave, CUtensorMapSwizzle,
                          CUtensorMapL2promotion, CUtensorMapFloatOOBfill);

void make_map(EncFn enc, CUtensorMap* m, const void* ptr, int rows, int cols, int box_rows, int box_cols, bool swz = true) {
    cuuint64_t gd[2] = {(cuuint64_t)cols, (cuuint64_t)rows};
    cuuint64_t gs[1] = {(cuuint64_t)cols * 2};
    cuuint32_t bx[2] = {(cuuint32_t)box_cols, (cuuint32_t)box_rows};
    cuuint32_t es[2] = {1, 1};
    enc(m, CU_TENSOR_MAP_DATA_TYPE_BFLOAT16, 2, const_cast<void*>(ptr), gd, gs, bx, es, CU_TENSOR_MAP_INTERLEAVE_NONE,
        swz ? CU_TENSOR_MAP_SWIZZLE_128B : CU_TENSOR_MAP_SWIZZLE_NONE, CU_TENSOR_MAP_L2_PROMOTION_L2_128B,
        CU_TENSOR_MAP_FLOAT_OOB_FILL_NONE);
}

}

extern "C" void kernel_launch(void* const* d_in, const int* in_sizes, int n_in, void* d_out, int out_size) {
    Ptrs pt;
    pt.x = (const __nv_bfloat16*)d_in[0];
    pt.hre = (const __nv_bfloat16*)d_in[3];
    pt.him = (const __nv_bfloat16*)d_in[4];
    pt.wg = (const __nv_bfloat16*)d_in[6];
    pt.wu = (const __nv_bfloat16*)d_in[7];
    pt.wd = (const __nv_bfloat16*)d_in[8];
    pt.out = (__nv_bfloat16*)d_out;

    void* fn = nullptr;
    cudaDriverEntryPointQueryResult qr;
    cudaGetDriverEntryPoint("cuTensorMapEncodeTiled", &fn, cudaEnableDefault, &qr);
    EncFn enc = (EncFn)fn;
    void *p_abT, *p_h;
    cudaGetSymbolAddress(&p_abT, g_abT);
    cudaGetSymbolAddress(&p_h, g_h);

    Maps tm;
    make_map(enc, &tm.wg, d_in[6], D_, F_, 64, 64);
    make_map(enc, &tm.wu, d_in[7], D_, F_, 64, 64);
    make_map(enc, &tm.hre, d_in[3], D_, D_, 64, 64);
    make_map(enc, &tm.him, d_in[4], D_, D_, 64, 64);
    make_map(enc, &tm.h, p_h, S_, F_, 128, 64);
    make_map(enc, &tm.abT, p_abT, 896, S_, 112, 64);
    make_map(enc, &tm.sre, d_in[1], S_, S_, 128, 64);
    make_map(enc, &tm.sim, d_in[2], S_, S_, 128, 64);
    make_map(enc, &tm.wd, d_in[8], F_, D_, 64, 64);

    cudaFuncSetAttribute(fused_kernel, cudaFuncAttributeMaxDynamicSharedMemorySize, SMEM_BYTES);

    cudaLaunchAttribute at[1];
    at[0].id = cudaLaunchAttributeClusterDimension;
    at[0].val.clusterDim.x = 2; at[0].val.clusterDim.y = 1; at[0].val.clusterDim.z = 1;
    cudaLaunchConfig_t cfg = {};
    cfg.gridDim = dim3(128); cfg.blockDim = dim3(384); cfg.stream = cudaStreamPerThread;
    cfg.attrs = at; cfg.numAttrs = 1;
    cfg.dynamicSmemBytes = SMEM_BYTES;
    cudaLaunchKernelEx(&cfg, fused_kernel, pt, tm);
}
```

```cpp
#include <cuda_runtime.h>
#include <cuda_bf16.h>
#include <cuda.h>
#include <stdint.h>

namespace {

constexpr int S_ = 2048, D_ = 448, F_ = 1792;

__device__ __align__(1024) __nv_bfloat16 g_abT[896 * 2048];
__device__ __align__(1024) __nv_bfloat16 g_h[2048 * 1792];
__device__ __align__(1024) __nv_bfloat16 g_y[2 * 2048 * 448];
struct Flags {
    unsigned int ab[16];
    unsigned int h[16 * 28];
    unsigned int y[32];
    unsigned int done;
};
__device__ Flags g_fl;

#define TL(k, i) do {} while (0)
__device__ __forceinline__ uint32_t s2u(const void* p) { return (uint32_t)__cvta_generic_to_shared(p); }
__device__ __forceinline__ void mbar_init(uint32_t b, int c) {
    asm volatile("mbarrier.init.shared::cta.b64 [%0], %1;" ::"r"(b), "r"(c));
}
__device__ __forceinline__ void mbar_expect(uint32_t b, uint32_t bytes) {
    asm volatile("mbarrier.arrive.expect_tx.shared::cta.b64 _, [%0], %1;" ::"r"(b), "r"(bytes) : "memory");
}
__device__ __forceinline__ void mbar_wait(uint32_t b, uint32_t ph) {
    uint32_t ok;
    do {
        asm volatile("{\n.reg .pred p;\nmbarrier.try_wait.parity.shared::cta.b64 p, [%1], %2;\nselp.u32 %0, 1, 0, p;\n}"
                     : "=r"(ok) : "r"(b), "r"(ph) : "memory");
    } while (!ok);
}
__device__ __forceinline__ void mbar_arrive_both(uint32_t b) {
    asm volatile("{\n.reg .b32 r0, r1;\n"
                 "mapa.shared::cluster.u32 r0, %0, 0;\n"
                 "mapa.shared::cluster.u32 r1, %0, 1;\n"
                 "mbarrier.arrive.shared::cluster.b64 _, [r0];\n"
                 "mbarrier.arrive.shared::cluster.b64 _, [r1];\n}"
                 ::"r"(b) : "memory");
}
__device__ __forceinline__ void tma_load(uint32_t dst, const CUtensorMap* m, uint32_t bar, int c0, int c1) {
    asm volatile("cp.async.bulk.tensor.2d.shared::cluster.global.mbarrier::complete_tx::bytes [%0], [%1, {%3, %4}], [%2];"
                 ::"r"(dst), "l"(m), "r"(bar), "r"(c0), "r"(c1) : "memory");
}
__device__ __forceinline__ void tma_load_mc(uint32_t dst, const CUtensorMap* m, uint32_t bar, int c0, int c1) {
    asm volatile("cp.async.bulk.tensor.2d.shared::cluster.global.mbarrier::complete_tx::bytes.multicast::cluster [%0], [%1, {%3, %4}], [%2], %5;"
                 ::"r"(dst), "l"(m), "r"(bar), "r"(c0), "r"(c1), "h"((uint16_t)3) : "memory");
}
__device__ __forceinline__ void tma_store(const CUtensorMap* m, uint32_t src, int c0, int c1) {
    asm volatile("cp.async.bulk.tensor.2d.global.shared::cta.bulk_group [%0, {%2, %3}], [%1];"
                 ::"l"(m), "r"(src), "r"(c0), "r"(c1) : "memory");
}
__device__ __forceinline__ void bulk_commit() { asm volatile("cp.async.bulk.commit_group;" ::: "memory"); }
__device__ __forceinline__ void bulk_wait_read0() { asm volatile("cp.async.bulk.wait_group.read 0;" ::: "memory"); }
__device__ __forceinline__ void bulk_wait0() { asm volatile("cp.async.bulk.wait_group 0;" ::: "memory"); }
__device__ __forceinline__ void fence_async() { asm volatile("fence.proxy.async.shared::cta;" ::: "memory"); }
__device__ __forceinline__ void fence_async_all() { asm volatile("fence.proxy.async;" ::: "memory"); }
__device__ __forceinline__ void cluster_sync() {
    asm volatile("barrier.cluster.arrive.release.aligned;\nbarrier.cluster.wait.acquire.aligned;" ::: "memory");
}
__device__ __forceinline__ void bar_sync(int id, int n) { asm volatile("bar.sync %0, %1;" ::"r"(id), "r"(n) : "memory"); }
__device__ __forceinline__ void wg_arrive() { asm volatile("wgmma.fence.sync.aligned;" ::: "memory"); }
__device__ __forceinline__ void wg_commit() { asm volatile("wgmma.commit_group.sync.aligned;" ::: "memory"); }
template <int N> __device__ __forceinline__ void wg_wait() { asm volatile("wgmma.wait_group.sync.aligned %0;" ::"n"(N) : "memory"); }
__device__ __forceinline__ void stmat4(uint32_t a, uint32_t r0, uint32_t r1, uint32_t r2, uint32_t r3) {
    asm volatile("stmatrix.sync.aligned.m8n8.x4.shared.b16 [%0], {%1, %2, %3, %4};" ::"r"(a), "r"(r0), "r"(r1), "r"(r2), "r"(r3) : "memory");
}
__device__ __forceinline__ void stmat4t(uint32_t a, uint32_t r0, uint32_t r1, uint32_t r2, uint32_t r3) {
    asm volatile("stmatrix.sync.aligned.m8n8.x4.trans.shared.b16 [%0], {%1, %2, %3, %4};" ::"r"(a), "r"(r0), "r"(r1), "r"(r2), "r"(r3) : "memory");
}
__device__ __forceinline__ void ldmat4(uint32_t a, uint32_t (&r)[4]) {
    asm volatile("ldmatrix.sync.aligned.m8n8.x4.shared.b16 {%0, %1, %2, %3}, [%4];"
                 : "=r"(r[0]), "=r"(r[1]), "=r"(r[2]), "=r"(r[3]) : "r"(a) : "memory");
}
__device__ __forceinline__ void flag_add(unsigned int* f) {
    asm volatile("red.release.gpu.global.add.u32 [%0], 1;" ::"l"(f) : "memory");
}
__device__ __forceinline__ void flag_wait(const unsigned int* f, unsigned int target) {
    unsigned int v;
    int spins = 0;
    while (true) {
        asm volatile("ld.acquire.gpu.global.u32 %0, [%1];" : "=r"(v) : "l"(f) : "memory");
        if ((int)(v - target) >= 0 || ++spins > (1 << 22)) break;
    }
}
__device__ __forceinline__ void quad_transpose(uint32_t (&r)[4], int q) {
    const bool o1 = q & 1, o2 = q & 2;
    uint32_t a = o1 ? r[0] : r[1], b = o1 ? r[2] : r[3];
    a = __shfl_xor_sync(0xffffffffu, a, 1);
    b = __shfl_xor_sync(0xffffffffu, b, 1);
    if (o1) { r[0] = a; r[2] = b; } else { r[1] = a; r[3] = b; }
    a = o2 ? r[0] : r[2]; b = o2 ? r[1] : r[3];
    a = __shfl_xor_sync(0xffffffffu, a, 2);
    b = __shfl_xor_sync(0xffffffffu, b, 2);
    if (o2) { r[0] = a; r[1] = b; } else { r[2] = a; r[3] = b; }
}
__device__ __forceinline__ uint32_t movmat_t(uint32_t v) {
    uint32_t r;
    asm volatile("movmatrix.sync.aligned.m8n8.trans.b16 %0, %1;" : "=r"(r) : "r"(v));
    return r;
}
__device__ __forceinline__ uint64_t mkdesc(uint32_t addr, uint32_t lbo, uint32_t sbo) {
    return (uint64_t)((addr & 0x3FFFF) >> 4) | ((uint64_t)(lbo >> 4) << 16) | ((uint64_t)(sbo >> 4) << 32) | (1ull << 62);
}
__device__ __forceinline__ uint32_t pack_bf16(float lo, float hi) {
    uint32_t r;
    asm("cvt.rn.bf16x2.f32 %0, %1, %2;" : "=r"(r) : "f"(hi), "f"(lo));
    return r;
}
__device__ __forceinline__ uint32_t hsub2(uint32_t a, uint32_t b) { uint32_t r; asm("sub.rn.bf16x2 %0, %1, %2;" : "=r"(r) : "r"(a), "r"(b)); return r; }
__device__ __forceinline__ uint32_t hadd2(uint32_t a, uint32_t b) { uint32_t r; asm("add.rn.bf16x2 %0, %1, %2;" : "=r"(r) : "r"(a), "r"(b)); return r; }
__device__ __forceinline__ uint32_t hmul2(uint32_t a, uint32_t b) { uint32_t r; asm("mul.rn.bf16x2 %0, %1, %2;" : "=r"(r) : "r"(a), "r"(b)); return r; }
__device__ __forceinline__ uint32_t hfma2(uint32_t a, uint32_t b, uint32_t c) { uint32_t r; asm("fma.rn.bf16x2 %0, %1, %2, %3;" : "=r"(r) : "r"(a), "r"(b), "r"(c)); return r; }
__device__ __forceinline__ float bf_lo(uint32_t u) { return __uint_as_float(u << 16); }
__device__ __forceinline__ float bf_hi(uint32_t u) { return __uint_as_float(u & 0xffff0000u); }
__device__ __forceinline__ float rbf(float v) { return __bfloat162float(__float2bfloat16_rn(v)); }
__device__ __forceinline__ float tanh_fast(float x) { float r; asm("tanh.approx.f32 %0, %1;" : "=f"(r) : "f"(x)); return r; }
__device__ __forceinline__ float gelu_tanh(float x) {
    float u = x * fmaf(x * x, 0.0356774081f, 0.7978845608f);
    float hx = 0.5f * x;
    return fmaf(hx, tanh_fast(u), hx);
}
__device__ __forceinline__ float silu(float f) { const float hf = 0.5f * f; return fmaf(hf, tanh_fast(hf), hf); }

template <int TB>
__device__ __forceinline__ void wgmma_n128(float (&d)[64], uint64_t da, uint64_t db, int scaleD) {
    asm volatile("{\n.reg .pred p;\nsetp.ne.b32 p, %66, 0;\n"
        "wgmma.mma_async.sync.aligned.m64n128k16.f32.bf16.bf16 {%0, %1, %2, %3, %4, %5, %6, %7, %8, %9, %10, %11, %12, %13, %14, %15, %16, %17, %18, %19, %20, %21, %22, %23, %24, %25, %26, %27, %28, %29, %30, %31, %32, %33, %34, %35, %36, %37, %38, %39, %40, %41, %42, %43, %44, %45, %46, %47, %48, %49, %50, %51, %52, %53, %54, %55, %56, %57, %58, %59, %60, %61, %62, %63}, %64, %65, p, 1, 1, 0, %67;\n}\n"
        : "+f"(d[0]), "+f"(d[1]), "+f"(d[2]), "+f"(d[3]), "+f"(d[4]), "+f"(d[5]), "+f"(d[6]), "+f"(d[7]), "+f"(d[8]), "+f"(d[9]), "+f"(d[10]), "+f"(d[11]), "+f"(d[12]), "+f"(d[13]), "+f"(d[14]), "+f"(d[15]), "+f"(d[16]), "+f"(d[17]), "+f"(d[18]), "+f"(d[19]), "+f"(d[20]), "+f"(d[21]), "+f"(d[22]), "+f"(d[23]), "+f"(d[24]), "+f"(d[25]), "+f"(d[26]), "+f"(d[27]), "+f"(d[28]), "+f"(d[29]), "+f"(d[30]), "+f"(d[31]), "+f"(d[32]), "+f"(d[33]), "+f"(d[34]), "+f"(d[35]), "+f"(d[36]), "+f"(d[37]), "+f"(d[38]), "+f"(d[39]), "+f"(d[40]), "+f"(d[41]), "+f"(d[42]), "+f"(d[43]), "+f"(d[44]), "+f"(d[45]), "+f"(d[46]), "+f"(d[47]), "+f"(d[48]), "+f"(d[49]), "+f"(d[50]), "+f"(d[51]), "+f"(d[52]), "+f"(d[53]), "+f"(d[54]), "+f"(d[55]), "+f"(d[56]), "+f"(d[57]), "+f"(d[58]), "+f"(d[59]), "+f"(d[60]), "+f"(d[61]), "+f"(d[62]), "+f"(d[63])
        : "l"(da), "l"(db), "r"(scaleD), "n"(TB));
}
template <int TB>
__device__ __forceinline__ void wgmma_n224(float (&d)[112], uint64_t da, uint64_t db, int scaleD) {
    asm volatile("{\n.reg .pred p;\nsetp.ne.b32 p, %114, 0;\n"
        "wgmma.mma_async.sync.aligned.m64n224k16.f32.bf16.bf16 {%0, %1, %2, %3, %4, %5, %6, %7, %8, %9, %10, %11, %12, %13, %14, %15, %16, %17, %18, %19, %20, %21, %22, %23, %24, %25, %26, %27, %28, %29, %30, %31, %32, %33, %34, %35, %36, %37, %38, %39, %40, %41, %42, %43, %44, %45, %46, %47, %48, %49, %50, %51, %52, %53, %54, %55, %56, %57, %58, %59, %60, %61, %62, %63, %64, %65, %66, %67, %68, %69, %70, %71, %72, %73, %74, %75, %76, %77, %78, %79, %80, %81, %82, %83, %84, %85, %86, %87, %88, %89, %90, %91, %92, %93, %94, %95, %96, %97, %98, %99, %100, %101, %102, %103, %104, %105, %106, %107, %108, %109, %110, %111}, %112, %113, p, 1, 1, 0, %115;\n}\n"
        : "+f"(d[0]), "+f"(d[1]), "+f"(d[2]), "+f"(d[3]), "+f"(d[4]), "+f"(d[5]), "+f"(d[6]), "+f"(d[7]), "+f"(d[8]), "+f"(d[9]), "+f"(d[10]), "+f"(d[11]), "+f"(d[12]), "+f"(d[13]), "+f"(d[14]), "+f"(d[15]), "+f"(d[16]), "+f"(d[17]), "+f"(d[18]), "+f"(d[19]), "+f"(d[20]), "+f"(d[21]), "+f"(d[22]), "+f"(d[23]), "+f"(d[24]), "+f"(d[25]), "+f"(d[26]), "+f"(d[27]), "+f"(d[28]), "+f"(d[29]), "+f"(d[30]), "+f"(d[31]), "+f"(d[32]), "+f"(d[33]), "+f"(d[34]), "+f"(d[35]), "+f"(d[36]), "+f"(d[37]), "+f"(d[38]), "+f"(d[39]), "+f"(d[40]), "+f"(d[41]), "+f"(d[42]), "+f"(d[43]), "+f"(d[44]), "+f"(d[45]), "+f"(d[46]), "+f"(d[47]), "+f"(d[48]), "+f"(d[49]), "+f"(d[50]), "+f"(d[51]), "+f"(d[52]), "+f"(d[53]), "+f"(d[54]), "+f"(d[55]), "+f"(d[56]), "+f"(d[57]), "+f"(d[58]), "+f"(d[59]), "+f"(d[60]), "+f"(d[61]), "+f"(d[62]), "+f"(d[63]), "+f"(d[64]), "+f"(d[65]), "+f"(d[66]), "+f"(d[67]), "+f"(d[68]), "+f"(d[69]), "+f"(d[70]), "+f"(d[71]), "+f"(d[72]), "+f"(d[73]), "+f"(d[74]), "+f"(d[75]), "+f"(d[76]), "+f"(d[77]), "+f"(d[78]), "+f"(d[79]), "+f"(d[80]), "+f"(d[81]), "+f"(d[82]), "+f"(d[83]), "+f"(d[84]), "+f"(d[85]), "+f"(d[86]), "+f"(d[87]), "+f"(d[88]), "+f"(d[89]), "+f"(d[90]), "+f"(d[91]), "+f"(d[92]), "+f"(d[93]), "+f"(d[94]), "+f"(d[95]), "+f"(d[96]), "+f"(d[97]), "+f"(d[98]), "+f"(d[99]), "+f"(d[100]), "+f"(d[101]), "+f"(d[102]), "+f"(d[103]), "+f"(d[104]), "+f"(d[105]), "+f"(d[106]), "+f"(d[107]), "+f"(d[108]), "+f"(d[109]), "+f"(d[110]), "+f"(d[111])
        : "l"(da), "l"(db), "r"(scaleD), "n"(TB));
}

constexpr int S1_STAGES = 7;
constexpr int S1_XN = 0;
constexpr int S1_B = 7 * 16384;
constexpr int Y_STAGES = 5, Y_STAGE = 45056;
constexpr int F_STAGES = 4, F_STAGE = 49152;
constexpr int BAR = S1_B + S1_STAGES * 16384;
constexpr int BAR_F1 = BAR, BAR_E1 = BAR + 56, BAR_F2 = BAR + 112, BAR_E2 = BAR + 152, BAR_S1DONE = BAR + 192;
constexpr int BAR_PUB = BAR + 208;
constexpr int DEP_CNT = BAR + 200;
constexpr int SMEM_BYTES = BAR + 256 + 1024;
constexpr int TPITCH = 464;

__device__ __forceinline__ int n_passes(int j) { return j < 6 ? 3 : (j == 6 ? 9 : 8); }
__device__ __forceinline__ int pass_slab(int j, int p) {
    if (p == 0) return j < 7 ? -1 : 0;
    if (p < 3) return 8 * p - 7 + j;
    return 17 + 2 * (p - 3) + (j - 6);
}

template <int TB>
__device__ __forceinline__ void s1_mainloop(float (&acc)[2][64], uint32_t sb, int idx, int lane, int handoff) {
    int st = idx % S1_STAGES;
    uint32_t ph = (idx / S1_STAGES) & 1;
    int prev = 0;
    uint64_t da = mkdesc(sb + S1_XN, 16, 1024);
    const uint64_t db0 = TB ? mkdesc(sb + S1_B, 8192, 1024) : mkdesc(sb + S1_B, 16, 1024);
#pragma unroll 1
    for (int kb = 0; kb < 7; kb++) {
        mbar_wait(sb + BAR_F1 + 8 * st, ph);
        if (kb == 6 && handoff) asm volatile("bar.arrive %0, 256;" ::"r"(handoff) : "memory");
        const uint64_t db = db0 + st * 1024;
        wg_arrive();
#pragma unroll
        for (int s = 0; s < 4; s++) {
            wgmma_n128<TB>(acc[0], da + s * 2, db + s * (TB ? 128 : 2), kb | s);
            wgmma_n128<TB>(acc[1], da + 512 + s * 2, db + s * (TB ? 128 : 2), kb | s);
        }
        wg_commit();
        wg_wait<1>();
        if (kb > 0 && lane == 0) mbar_arrive_both(sb + BAR_E1 + 8 * prev);
        prev = st;
        da += 1024;
        if (++st == S1_STAGES) { st = 0; ph ^= 1; }
    }
    wg_wait<0>();
    if (lane == 0) mbar_arrive_both(sb + BAR_E1 + 8 * prev);
}

template <int TB>
__device__ __forceinline__ void s2_mainloop(float (&acc)[112], uint32_t sb, int wg, int lane) {
    constexpr int NST = TB ? F_STAGES : Y_STAGES, SSZ = TB ? F_STAGE : Y_STAGE, NKB = TB ? 28 : 32;
    int st = 0;
    uint32_t ph = 0;
    int prev = 0;
    const uint64_t da0 = mkdesc(sb + wg * 8192, 16, 1024);
    const uint64_t db0 = TB ? mkdesc(sb + 16384, 8192, 1024) : mkdesc(sb + 16384, 16, 1024);
#pragma unroll 1
    for (int i = 0; i < NKB; i++) {
        mbar_wait(sb + BAR_F2 + 8 * st, ph);
        const uint64_t da = da0 + st * (SSZ / 16), db = db0 + st * (SSZ / 16);
        wg_arrive();
#pragma unroll
        for (int s = 0; s < 4; s++) wgmma_n224<TB>(acc, da + s * 2, db + s * (TB ? 128 : 2), i | s);
        wg_commit();
        wg_wait<1>();
        if (i > 0 && lane == 0) mbar_arrive_both(sb + BAR_E2 + 8 * prev);
        prev = st;
        if (++st == NST) { st = 0; ph ^= 1; }
    }
    wg_wait<0>();
}

struct Maps {
    CUtensorMap wg, wu, hre, him, h, abT, sre, sim, wd;
};
struct Ptrs {
    const __nv_bfloat16 *x, *hre, *him, *wg, *wu, *wd;
    __nv_bfloat16* out;
};
__device__ __forceinline__ void mbar_arrive(uint32_t b) {
    asm volatile("mbarrier.arrive.shared::cta.b64 _, [%0];" ::"r"(b) : "memory");
}
__device__ __forceinline__ void l2_prefetch(const void* p, uint32_t bytes) {
    asm volatile("cp.async.bulk.prefetch.L2.global [%0], %1;" ::"l"(p), "r"(bytes) : "memory");
}
__device__ __forceinline__ void tma_prefetch(const CUtensorMap* m, int c0, int c1) {
    asm volatile("cp.async.bulk.prefetch.tensor.2d.L2.global.tile [%0, {%1, %2}];" ::"l"(m), "r"(c0), "r"(c1) : "memory");
}

__device__ __forceinline__ void dep_wait(uint32_t sb, uint32_t need) {
    uint32_t v;
    do { asm volatile("ld.acquire.cta.shared.u32 %0, [%1];" : "=r"(v) : "r"(sb + DEP_CNT) : "memory"); } while (v < need);
}

__global__ void __launch_bounds__(384, 1)
fused_kernel(const __grid_constant__ Ptrs pt, const __grid_constant__ Maps tm) {
    extern __shared__ unsigned char smem_raw[];
    const uint32_t sb = (s2u(smem_raw) + 1023) & ~1023u;
    const int tid = threadIdx.x, lane = tid & 31;
    const int warp = __shfl_sync(0xffffffffu, tid >> 5, 0);
    const int rank = blockIdx.x & 1;
    const int cid = blockIdx.x >> 1;
    const int j = cid & 7;
    const int rb = (cid >> 3) * 2 + rank;
    const int npass = n_passes(j);
    const int n = j & 1;
    const int part = j >> 1;

    {
        const int l8 = lane & 7, sub = lane >> 3;
        uint4 v[3][7];
#pragma unroll
        for (int it = 0; it < 3; it++) {
            const int qd = warp + 12 * it;
            if (qd < 32) {
                const uint4* src = reinterpret_cast<const uint4*>(pt.x + (size_t)(rb * 128 + qd * 4 + sub) * D_) + l8;
#pragma unroll
                for (int i = 0; i < 7; i++) v[it][i] = __ldg(src + i * 8);
            }
        }
        if (tid == 256) {
            TL(0, 0);
            for (int i = 0; i < S1_STAGES; i++) { mbar_init(sb + BAR_F1 + 8 * i, 1); mbar_init(sb + BAR_E1 + 8 * i, 8); }
            for (int i = 0; i < Y_STAGES; i++) { mbar_init(sb + BAR_F2 + 8 * i, 1); mbar_init(sb + BAR_E2 + 8 * i, 16); }
            mbar_init(sb + BAR_S1DONE, 16);
            mbar_init(sb + BAR_PUB, 4);
            mbar_init(sb + BAR_PUB + 8, 4);
            asm volatile("st.shared.u32 [%0], %1;" ::"r"(sb + DEP_CNT), "r"(0) : "memory");
            asm volatile("fence.mbarrier_init.release.cluster;" ::: "memory");
        }
        __syncwarp();
        asm volatile("barrier.cluster.arrive.relaxed.aligned;\nbarrier.cluster.wait.aligned;" ::: "memory");
        if (tid == 256) {
            const int slab = pass_slab(j, 0);
            for (int kb = 0; kb < 7; kb++) {
                const uint32_t dst = sb + S1_B + kb * 16384 + rank * 8192;
                const uint32_t fb = sb + BAR_F1 + 8 * kb;
                mbar_expect(fb, 16384);
                if (slab >= 0) {
                    tma_load_mc(dst, rank ? &tm.wu : &tm.wg, fb, slab * 64, kb * 64);
                } else {
                    const int a = 2 * j + rank;
                    tma_load_mc(dst, a < 7 ? &tm.hre : &tm.him, fb, kb * 64, (a < 7 ? a : a - 7) * 64);
                }
            }
            const int b = blockIdx.x;
            l2_prefetch((const char*)pt.wg + b * 12544, 12544);
            l2_prefetch((const char*)pt.wu + b * 12544, 12544);
            l2_prefetch((const char*)pt.wd + b * 12544, 12544);
        }
        __syncwarp();
        if (tid == 0) TL(0, 1);
#pragma unroll
        for (int it = 0; it < 3; it++) {
            const int qd = warp + 12 * it;
            if (qd < 32) {
                const int row = qd * 4 + sub;
                float s0 = 0.f, s1 = 0.f;
#pragma unroll
                for (int i = 0; i < 7; i++) {
                    s0 += (bf_lo(v[it][i].x) + bf_hi(v[it][i].x)) + (bf_lo(v[it][i].y) + bf_hi(v[it][i].y));
                    s1 += (bf_lo(v[it][i].z) + bf_hi(v[it][i].z)) + (bf_lo(v[it][i].w) + bf_hi(v[it][i].w));
                }
                float s = s0 + s1;
                s += __shfl_xor_sync(0xffffffffu, s, 1);
                s += __shfl_xor_sync(0xffffffffu, s, 2);
                s += __shfl_xor_sync(0xffffffffu, s, 4);
                if (it == 0 && tid == 0) TL(0, 3);
                const float mean = s * (1.0f / D_);
                float q0 = 0.f, q1 = 0.f;
#pragma unroll
                for (int i = 0; i < 7; i++) {
                    const uint32_t w[4] = {v[it][i].x, v[it][i].y, v[it][i].z, v[it][i].w};
#pragma unroll
                    for (int c = 0; c < 4; c++) {
                        const float d0 = bf_lo(w[c]) - mean, d1 = bf_hi(w[c]) - mean;
                        q0 = fmaf(d0, d0, q0);
                        q1 = fmaf(d1, d1, q1);
                    }
                }
                float q = q0 + q1;
                q += __shfl_xor_sync(0xffffffffu, q, 1);
                q += __shfl_xor_sync(0xffffffffu, q, 2);
                q += __shfl_xor_sync(0xffffffffu, q, 4);
                const float var = rbf(q * (1.0f / D_));
                const float den = rbf(sqrtf(rbf(var + 1e-5f)));
                const float rinv = 1.0f / den;
                const float rhi = rbf(rinv);
                const uint32_t m2 = pack_bf16(mean, mean), rhi2 = pack_bf16(rhi, rhi), rlo2 = pack_bf16(rinv - rhi, rinv - rhi);
                const uint32_t dst = sb + S1_XN + row * 128 + ((l8 ^ (row & 7)) << 4);
#pragma unroll
                for (int i = 0; i < 7; i++) {
                    const uint32_t w[4] = {v[it][i].x, v[it][i].y, v[it][i].z, v[it][i].w};
                    uint32_t o[4];
#pragma unroll
                    for (int c = 0; c < 4; c++) {
                        const uint32_t xc = hsub2(w[c], m2);
                        o[c] = hfma2(xc, rhi2, hmul2(xc, rlo2));
                    }
                    asm volatile("st.shared.v4.b32 [%0], {%1, %2, %3, %4};" ::"r"(dst + i * 16384), "r"(o[0]), "r"(o[1]), "r"(o[2]), "r"(o[3]) : "memory");
                }
            }
        }
        fence_async();
        __syncthreads();
        if (tid == 0) TL(0, 2);
    }

    if (warp >= 8) {
        asm volatile("setmaxnreg.dec.sync.aligned.u32 40;");
        if (warp == 8) {
            if (lane == 0) {
                int st = 0;
                uint32_t ph = 0;
                for (int p = 1; p < npass; p++) {
                    const int slab = pass_slab(j, p);
                    for (int kb = 0; kb < 7; kb++) {
                        mbar_wait(sb + BAR_E1 + 8 * st, ph);
                        const uint32_t fb = sb + BAR_F1 + 8 * st;
                        mbar_expect(fb, 16384);
                        tma_load_mc(sb + S1_B + st * 16384 + rank * 8192, rank ? &tm.wu : &tm.wg, fb, slab * 64, kb * 64);
                        if (++st == S1_STAGES) { st = 0; ph ^= 1; }
                    }
                }
                if (part < 3) {
                    mbar_wait(sb + BAR_S1DONE, 0);
                    TL(0, 24);
                    st = 0; ph = 1;
                    if (part < 2) {
                        const CUtensorMap* ma = part ? &tm.sim : &tm.sre;
                        for (int g = 0; g < 32; g++) {
                            mbar_wait(sb + BAR_E2 + 8 * st, ph);
                            const uint32_t dst = sb + st * Y_STAGE;
                            const uint32_t fb = sb + BAR_F2 + 8 * st;
                            mbar_expect(fb, Y_STAGE);
                            tma_load(dst, ma, fb, g * 64, rb * 128);
                            dep_wait(sb, (g >> 1) + 1);
                            tma_load_mc(dst + 16384 + rank * 14336, &tm.abT, fb, g * 64, part * 448 + n * 224 + rank * 112);
                            if (++st == Y_STAGES) { st = 0; ph ^= 1; }
                        }
                    } else {
                        for (int g = 0; g < 28; g++) {
                            mbar_wait(sb + BAR_E2 + 8 * st, ph);
                            const uint32_t dst = sb + st * F_STAGE;
                            const uint32_t fb = sb + BAR_F2 + 8 * st;
                            mbar_expect(fb, F_STAGE);
                            tma_load_mc(dst + 16384 + (2 * rank) * 8192, &tm.wd, fb, n * 224 + (2 * rank) * 64, g * 64);
                            tma_load_mc(dst + 16384 + (2 * rank + 1) * 8192, &tm.wd, fb, n * 224 + (2 * rank + 1) * 64, g * 64);
                            dep_wait(sb, g + 1);
                            tma_load(dst, &tm.h, fb, g * 64, rb * 128);
                            if (++st == F_STAGES) { st = 0; ph ^= 1; }
                        }
                    }
                }
            }
        } else if (warp == 9) {
            if (lane == 0 && part < 3) {
                if (part < 2) {
                    const CUtensorMap* ma = part ? &tm.sim : &tm.sre;
                    for (int q = 0; q < 16; q++) tma_prefetch(ma, (2 * q + n) * 64, rb * 128);
                }
                const int ndep = part < 2 ? 16 : 28;
                const unsigned int* f = part < 2 ? g_fl.ab : g_fl.h + rb * 28;
                const unsigned int epoch = *(volatile unsigned int*)&g_fl.done / gridDim.x + 1;
                const unsigned int target = (part < 2 ? 7 : 1) * epoch;
                for (int d = 0; d < ndep; d++) {
                    flag_wait(f + d, target);
                    fence_async_all();
                    asm volatile("st.release.cta.shared.u32 [%0], %1;" ::"r"(sb + DEP_CNT), "r"(d + 1) : "memory");
                }
                if (part == 2) {
                    flag_wait(&g_fl.y[rb * 2 + n], 16 * epoch);
                    asm volatile("st.release.cta.shared.u32 [%0], %1;" ::"r"(sb + DEP_CNT), "r"(29) : "memory");
                }
            }
        } else {
            if (lane == 0) {
                const int w = warp - 10;
                uint32_t ph = 0;
                for (int p = w; p < npass; p += 2) {
                    const int slab = pass_slab(j, p);
                    mbar_wait(sb + BAR_PUB + 8 * w, ph);
                    ph ^= 1;
                    __threadfence();
                    flag_add(slab >= 0 ? &g_fl.h[rb * 28 + slab] : &g_fl.ab[rb]);
                }
            }
        }
        __syncwarp();
    } else {
        asm volatile("setmaxnreg.inc.sync.aligned.u32 232;");
        const int wg = warp >> 2, wl = warp & 3, wtid = tid & 127;
        const int qd = lane & 3;
        {
            float acc[2][64];
            for (int p = wg; p < npass; p += 2) {
                const int slab = pass_slab(j, p);
                if (p > 0) bar_sync(4 + (p & 1), 256);
                const int handoff = (p + 1 < npass) ? 4 + ((p + 1) & 1) : 0;
                if (slab >= 0) s1_mainloop<1>(acc, sb, p * 7, lane, handoff);
                else s1_mainloop<0>(acc, sb, p * 7, lane, handoff);
                if (p + 2 >= npass && lane == 0) mbar_arrive_both(sb + BAR_S1DONE);
                if (wtid == 0 && p < 4) TL(0, 4 + p);

                if (slab >= 0) {
                    __nv_bfloat16* dst = g_h + (size_t)(rb * 128 + wl * 16 + (lane >> 2)) * F_ + slab * 64 + qd * 8;
#pragma unroll
                    for (int mh = 0; mh < 2; mh++) {
#pragma unroll
                        for (int hh = 0; hh < 2; hh++) {
#pragma unroll
                            for (int g4 = 0; g4 < 2; g4++) {
                                uint32_t r[4];
#pragma unroll
                                for (int t = 0; t < 4; t++) {
                                    const int o = (g4 * 4 + t) * 4 + hh * 2;
                                    const uint32_t g2 = pack_bf16(acc[mh][o], acc[mh][o + 1]);
                                    const uint32_t u2 = pack_bf16(acc[mh][32 + o], acc[mh][32 + o + 1]);
                                    const uint32_t a2 = pack_bf16(gelu_tanh(bf_lo(g2)), gelu_tanh(bf_hi(g2)));
                                    r[t] = hmul2(a2, u2);
                                }
                                quad_transpose(r, qd);
                                __stcg(reinterpret_cast<uint4*>(dst + (size_t)(mh * 64 + hh * 8) * F_ + g4 * 32), make_uint4(r[0], r[1], r[2], r[3]));
                            }
                        }
                    }
                } else {
                    __nv_bfloat16* dst = g_abT + (size_t)(j * 128 + (qd >> 1) * 8 + (lane >> 2)) * S_ + rb * 128 + wl * 16 + (qd & 1) * 8;
#pragma unroll
                    for (int mh = 0; mh < 2; mh++) {
#pragma unroll
                        for (int jj = 0; jj < 16; jj += 2) {
                            uint32_t r[4];
#pragma unroll
                            for (int t = 0; t < 4; t++) {
                                const int o = (jj + (t >> 1)) * 4 + (t & 1) * 2;
                                r[t] = movmat_t(pack_bf16(acc[mh][o], acc[mh][o + 1]));
                            }
                            quad_transpose(r, qd);
                            __stcg(reinterpret_cast<uint4*>(dst + (size_t)(jj * 8) * S_ + mh * 64), make_uint4(r[0], r[1], r[2], r[3]));
                        }
                    }
                }
                __syncwarp();
                if (lane == 0) mbar_arrive(sb + BAR_PUB + 8 * wg);
                if (wtid == 0 && p < 4) TL(0, 10 + p);
            }
        }
        if (wtid == 0) TL(0, 20 + wg);
        if (part < 3) {
            {
                float acc[112];
                const size_t base = (size_t)(rb * 128 + wg * 64 + wl * 16 + (lane >> 2)) * D_ + n * 224 + qd * 8;
                if (part < 2) {
                    s2_mainloop<0>(acc, sb, wg, lane);
                    if (tid == 0) TL(0, 25);
                    __nv_bfloat16* dst = g_y + (size_t)part * S_ * D_ + base;
#pragma unroll
                    for (int hh = 0; hh < 2; hh++) {
#pragma unroll
                        for (int g4 = 0; g4 < 7; g4++) {
                            uint32_t r[4];
#pragma unroll
                            for (int t = 0; t < 4; t++) r[t] = pack_bf16(acc[(g4 * 4 + t) * 4 + hh * 2], acc[(g4 * 4 + t) * 4 + hh * 2 + 1]);
                            quad_transpose(r, qd);
                            __stcg(reinterpret_cast<uint4*>(dst + (size_t)(hh * 8) * D_ + g4 * 32), make_uint4(r[0], r[1], r[2], r[3]));
                        }
                    }
                    __threadfence();
                    __syncwarp();
                    if (lane == 0) flag_add(&g_fl.y[rb * 2 + n]);
                } else {
                    uint4 xv[14];
#pragma unroll
                    for (int i = 0; i < 14; i++)
                        xv[i] = __ldg(reinterpret_cast<const uint4*>(pt.x + base + (i / 7) * 8 * D_ + (i % 7) * 32));
                    s2_mainloop<1>(acc, sb, wg, lane);
                    if (tid == 0) TL(0, 25);
                    dep_wait(sb, 29);
                    if (tid == 0) TL(0, 26);
                    uint32_t gq[56];
#pragma unroll
                    for (int hh = 0; hh < 2; hh++) {
                        uint4 yr[7], yi[7];
#pragma unroll
                        for (int i = 0; i < 7; i++) {
                            yr[i] = __ldcg(reinterpret_cast<const uint4*>(g_y + base + hh * 8 * D_ + i * 32));
                            yi[i] = __ldcg(reinterpret_cast<const uint4*>(g_y + (size_t)S_ * D_ + base + hh * 8 * D_ + i * 32));
                        }
                        if (hh == 0) {
#pragma unroll
                            for (int i = 0; i < 56; i++) {
                                const uint32_t f2 = pack_bf16(acc[2 * i], acc[2 * i + 1]);
                                gq[i] = pack_bf16(silu(bf_lo(f2)), silu(bf_hi(f2)));
                            }
                        }
#pragma unroll
                        for (int g4 = 0; g4 < 7; g4++) {
                            uint32_t r[4];
#pragma unroll
                            for (int t = 0; t < 4; t++) r[t] = gq[(g4 * 4 + t) * 2 + hh];
                            quad_transpose(r, qd);
                            const uint4 xx = xv[hh * 7 + g4];
                            uint4 o;
                            o.x = hadd2(xx.x, hmul2(hsub2(yr[g4].x, yi[g4].x), r[0]));
                            o.y = hadd2(xx.y, hmul2(hsub2(yr[g4].y, yi[g4].y), r[1]));
                            o.z = hadd2(xx.z, hmul2(hsub2(yr[g4].z, yi[g4].z), r[2]));
                            o.w = hadd2(xx.w, hmul2(hsub2(yr[g4].w, yi[g4].w), r[3]));
                            *reinterpret_cast<uint4*>(pt.out + base + hh * 8 * D_ + g4 * 32) = o;
                        }
                    }
                }
            }
        }
    }
    if (tid == 0) TL(0, 29);
    cluster_sync();
    if (tid == 0) {
        TL(0, 30);
        atomicAdd(&g_fl.done, 1u);
    }
}

typedef CUresult (*EncFn)(CUtensorMap*, CUtensorMapDataType, cuuint32_t, void*, const cuuint64_t*, const cuuint64_t*,
                          const cuuint32_t*, const cuuint32_t*, CUtensorMapInterleave, CUtensorMapSwizzle,
                          CUtensorMapL2promotion, CUtensorMapFloatOOBfill);

void make_map(EncFn enc, CUtensorMap* m, const void* ptr, int rows, int cols, int box_rows, int box_cols, bool swz = true) {
    cuuint64_t gd[2] = {(cuuint64_t)cols, (cuuint64_t)rows};
    cuuint64_t gs[1] = {(cuuint64_t)cols * 2};
    cuuint32_t bx[2] = {(cuuint32_t)box_cols, (cuuint32_t)box_rows};
    cuuint32_t es[2] = {1, 1};
    enc(m, CU_TENSOR_MAP_DATA_TYPE_BFLOAT16, 2, const_cast<void*>(ptr), gd, gs, bx, es, CU_TENSOR_MAP_INTERLEAVE_NONE,
        swz ? CU_TENSOR_MAP_SWIZZLE_128B : CU_TENSOR_MAP_SWIZZLE_NONE, CU_TENSOR_MAP_L2_PROMOTION_L2_128B,
        CU_TENSOR_MAP_FLOAT_OOB_FILL_NONE);
}

}

extern "C" void kernel_launch(void* const* d_in, const int* in_sizes, int n_in, void* d_out, int out_size) {
    Ptrs pt;
    pt.x = (const __nv_bfloat16*)d_in[0];
    pt.hre = (const __nv_bfloat16*)d_in[3];
    pt.him = (const __nv_bfloat16*)d_in[4];
    pt.wg = (const __nv_bfloat16*)d_in[6];
    pt.wu = (const __nv_bfloat16*)d_in[7];
    pt.wd = (const __nv_bfloat16*)d_in[8];
    pt.out = (__nv_bfloat16*)d_out;

    void* fn = nullptr;
    cudaDriverEntryPointQueryResult qr;
    cudaGetDriverEntryPoint("cuTensorMapEncodeTiled", &fn, cudaEnableDefault, &qr);
    EncFn enc = (EncFn)fn;
    void *p_abT, *p_h;
    cudaGetSymbolAddress(&p_abT, g_abT);
    cudaGetSymbolAddress(&p_h, g_h);

    Maps tm;
    make_map(enc, &tm.wg, d_in[6], D_, F_, 64, 64);
    make_map(enc, &tm.wu, d_in[7], D_, F_, 64, 64);
    make_map(enc, &tm.hre, d_in[3], D_, D_, 64, 64);
    make_map(enc, &tm.him, d_in[4], D_, D_, 64, 64);
    make_map(enc, &tm.h, p_h, S_, F_, 128, 64);
    make_map(enc, &tm.abT, p_abT, 896, S_, 112, 64);
    make_map(enc, &tm.sre, d_in[1], S_, S_, 128, 64);
    make_map(enc, &tm.sim, d_in[2], S_, S_, 128, 64);
    make_map(enc, &tm.wd, d_in[8], F_, D_, 64, 64);

    cudaFuncSetAttribute(fused_kernel, cudaFuncAttributeMaxDynamicSharedMemorySize, SMEM_BYTES);

    cudaLaunchAttribute at[1];
    at[0].id = cudaLaunchAttributeClusterDimension;
    at[0].val.clusterDim.x = 2; at[0].val.clusterDim.y = 1; at[0].val.clusterDim.z = 1;
    cudaLaunchConfig_t cfg = {};
    cfg.gridDim = dim3(128); cfg.blockDim = dim3(384); cfg.stream = cudaStreamPerThread;
    cfg.attrs = at; cfg.numAttrs = 1;
    cfg.dynamicSmemBytes = SMEM_BYTES;
    cudaLaunchKernelEx(&cfg, fused_kernel, pt, tm);
}
```

```cpp
#include <cuda_runtime.h>
#include <cuda_bf16.h>
#include <cuda.h>
#include <stdint.h>

namespace {

constexpr int S_ = 2048, D_ = 448, F_ = 1792;

__device__ __align__(1024) __nv_bfloat16 g_abT[896 * 2048];
__device__ __align__(1024) __nv_bfloat16 g_h[2048 * 1792];
__device__ __align__(1024) __nv_bfloat16 g_y[2 * 2048 * 448];
struct Flags {
    unsigned int ab[16];
    unsigned int h[16 * 28];
    unsigned int y[32];
    unsigned int done;
};
__device__ Flags g_fl;

#define TL(k, i) do {} while (0)
__device__ __forceinline__ uint32_t s2u(const void* p) { return (uint32_t)__cvta_generic_to_shared(p); }
__device__ __forceinline__ void mbar_init(uint32_t b, int c) {
    asm volatile("mbarrier.init.shared::cta.b64 [%0], %1;" ::"r"(b), "r"(c));
}
__device__ __forceinline__ void mbar_expect(uint32_t b, uint32_t bytes) {
    asm volatile("mbarrier.arrive.expect_tx.shared::cta.b64 _, [%0], %1;" ::"r"(b), "r"(bytes) : "memory");
}
__device__ __forceinline__ void mbar_wait(uint32_t b, uint32_t ph) {
    uint32_t ok;
    do {
        asm volatile("{\n.reg .pred p;\nmbarrier.try_wait.parity.shared::cta.b64 p, [%1], %2;\nselp.u32 %0, 1, 0, p;\n}"
                     : "=r"(ok) : "r"(b), "r"(ph) : "memory");
    } while (!ok);
}
__device__ __forceinline__ void mbar_arrive_both(uint32_t b) {
    asm volatile("{\n.reg .b32 r0, r1;\n"
                 "mapa.shared::cluster.u32 r0, %0, 0;\n"
                 "mapa.shared::cluster.u32 r1, %0, 1;\n"
                 "mbarrier.arrive.shared::cluster.b64 _, [r0];\n"
                 "mbarrier.arrive.shared::cluster.b64 _, [r1];\n}"
                 ::"r"(b) : "memory");
}
__device__ __forceinline__ void tma_load(uint32_t dst, const CUtensorMap* m, uint32_t bar, int c0, int c1) {
    asm volatile("cp.async.bulk.tensor.2d.shared::cluster.global.mbarrier::complete_tx::bytes [%0], [%1, {%3, %4}], [%2];"
                 ::"r"(dst), "l"(m), "r"(bar), "r"(c0), "r"(c1) : "memory");
}
__device__ __forceinline__ void tma_load_mc(uint32_t dst, const CUtensorMap* m, uint32_t bar, int c0, int c1) {
    asm volatile("cp.async.bulk.tensor.2d.shared::cluster.global.mbarrier::complete_tx::bytes.multicast::cluster [%0], [%1, {%3, %4}], [%2], %5;"
                 ::"r"(dst), "l"(m), "r"(bar), "r"(c0), "r"(c1), "h"((uint16_t)3) : "memory");
}
__device__ __forceinline__ void tma_store(const CUtensorMap* m, uint32_t src, int c0, int c1) {
    asm volatile("cp.async.bulk.tensor.2d.global.shared::cta.bulk_group [%0, {%2, %3}], [%1];"
                 ::"l"(m), "r"(src), "r"(c0), "r"(c1) : "memory");
}
__device__ __forceinline__ void bulk_commit() { asm volatile("cp.async.bulk.commit_group;" ::: "memory"); }
__device__ __forceinline__ void bulk_wait_read0() { asm volatile("cp.async.bulk.wait_group.read 0;" ::: "memory"); }
__device__ __forceinline__ void bulk_wait0() { asm volatile("cp.async.bulk.wait_group 0;" ::: "memory"); }
__device__ __forceinline__ void fence_async() { asm volatile("fence.proxy.async.shared::cta;" ::: "memory"); }
__device__ __forceinline__ void fence_async_all() { asm volatile("fence.proxy.async;" ::: "memory"); }
__device__ __forceinline__ void cluster_sync() {
    asm volatile("barrier.cluster.arrive.release.aligned;\nbarrier.cluster.wait.acquire.aligned;" ::: "memory");
}
__device__ __forceinline__ void bar_sync(int id, int n) { asm volatile("bar.sync %0, %1;" ::"r"(id), "r"(n) : "memory"); }
__device__ __forceinline__ void wg_arrive() { asm volatile("wgmma.fence.sync.aligned;" ::: "memory"); }
__device__ __forceinline__ void wg_commit() { asm volatile("wgmma.commit_group.sync.aligned;" ::: "memory"); }
template <int N> __device__ __forceinline__ void wg_wait() { asm volatile("wgmma.wait_group.sync.aligned %0;" ::"n"(N) : "memory"); }
__device__ __forceinline__ void stmat4(uint32_t a, uint32_t r0, uint32_t r1, uint32_t r2, uint32_t r3) {
    asm volatile("stmatrix.sync.aligned.m8n8.x4.shared.b16 [%0], {%1, %2, %3, %4};" ::"r"(a), "r"(r0), "r"(r1), "r"(r2), "r"(r3) : "memory");
}
__device__ __forceinline__ void stmat4t(uint32_t a, uint32_t r0, uint32_t r1, uint32_t r2, uint32_t r3) {
    asm volatile("stmatrix.sync.aligned.m8n8.x4.trans.shared.b16 [%0], {%1, %2, %3, %4};" ::"r"(a), "r"(r0), "r"(r1), "r"(r2), "r"(r3) : "memory");
}
__device__ __forceinline__ void ldmat4(uint32_t a, uint32_t (&r)[4]) {
    asm volatile("ldmatrix.sync.aligned.m8n8.x4.shared.b16 {%0, %1, %2, %3}, [%4];"
                 : "=r"(r[0]), "=r"(r[1]), "=r"(r[2]), "=r"(r[3]) : "r"(a) : "memory");
}
__device__ __forceinline__ void flag_add(unsigned int* f) {
    asm volatile("red.release.gpu.global.add.u32 [%0], 1;" ::"l"(f) : "memory");
}
__device__ __forceinline__ void flag_wait(const unsigned int* f, unsigned int target) {
    unsigned int v;
    int spins = 0;
    while (true) {
        asm volatile("ld.acquire.gpu.global.u32 %0, [%1];" : "=r"(v) : "l"(f) : "memory");
        if ((int)(v - target) >= 0 || ++spins > (1 << 22)) break;
    }
}
__device__ __forceinline__ void quad_transpose(uint32_t (&r)[4], int q) {
    const bool o1 = q & 1, o2 = q & 2;
    uint32_t a = o1 ? r[0] : r[1], b = o1 ? r[2] : r[3];
    a = __shfl_xor_sync(0xffffffffu, a, 1);
    b = __shfl_xor_sync(0xffffffffu, b, 1);
    if (o1) { r[0] = a; r[2] = b; } else { r[1] = a; r[3] = b; }
    a = o2 ? r[0] : r[2]; b = o2 ? r[1] : r[3];
    a = __shfl_xor_sync(0xffffffffu, a, 2);
    b = __shfl_xor_sync(0xffffffffu, b, 2);
    if (o2) { r[0] = a; r[1] = b; } else { r[2] = a; r[3] = b; }
}
__device__ __forceinline__ uint32_t movmat_t(uint32_t v) {
    uint32_t r;
    asm volatile("movmatrix.sync.aligned.m8n8.trans.b16 %0, %1;" : "=r"(r) : "r"(v));
    return r;
}
__device__ __forceinline__ uint64_t mkdesc(uint32_t addr, uint32_t lbo, uint32_t sbo) {
    return (uint64_t)((addr & 0x3FFFF) >> 4) | ((uint64_t)(lbo >> 4) << 16) | ((uint64_t)(sbo >> 4) << 32) | (1ull << 62);
}
__device__ __forceinline__ uint32_t pack_bf16(float lo, float hi) {
    uint32_t r;
    asm("cvt.rn.bf16x2.f32 %0, %1, %2;" : "=r"(r) : "f"(hi), "f"(lo));
    return r;
}
__device__ __forceinline__ uint32_t hsub2(uint32_t a, uint32_t b) { uint32_t r; asm("sub.rn.bf16x2 %0, %1, %2;" : "=r"(r) : "r"(a), "r"(b)); return r; }
__device__ __forceinline__ uint32_t hadd2(uint32_t a, uint32_t b) { uint32_t r; asm("add.rn.bf16x2 %0, %1, %2;" : "=r"(r) : "r"(a), "r"(b)); return r; }
__device__ __forceinline__ uint32_t hmul2(uint32_t a, uint32_t b) { uint32_t r; asm("mul.rn.bf16x2 %0, %1, %2;" : "=r"(r) : "r"(a), "r"(b)); return r; }
__device__ __forceinline__ uint32_t hfma2(uint32_t a, uint32_t b, uint32_t c) { uint32_t r; asm("fma.rn.bf16x2 %0, %1, %2, %3;" : "=r"(r) : "r"(a), "r"(b), "r"(c)); return r; }
__device__ __forceinline__ float bf_lo(uint32_t u) { return __uint_as_float(u << 16); }
__device__ __forceinline__ float bf_hi(uint32_t u) { return __uint_as_float(u & 0xffff0000u); }
__device__ __forceinline__ float rbf(float v) { return __bfloat162float(__float2bfloat16_rn(v)); }
__device__ __forceinline__ float tanh_fast(float x) { float r; asm("tanh.approx.f32 %0, %1;" : "=f"(r) : "f"(x)); return r; }
__device__ __forceinline__ float gelu_tanh(float x) {
    float u = x * fmaf(x * x, 0.0356774081f, 0.7978845608f);
    float hx = 0.5f * x;
    return fmaf(hx, tanh_fast(u), hx);
}
__device__ __forceinline__ float silu(float f) { const float hf = 0.5f * f; return fmaf(hf, tanh_fast(hf), hf); }

template <int TB>
__device__ __forceinline__ void wgmma_n128(float (&d)[64], uint64_t da, uint64_t db, int scaleD) {
    asm volatile("{\n.reg .pred p;\nsetp.ne.b32 p, %66, 0;\n"
        "wgmma.mma_async.sync.aligned.m64n128k16.f32.bf16.bf16 {%0, %1, %2, %3, %4, %5, %6, %7, %8, %9, %10, %11, %12, %13, %14, %15, %16, %17, %18, %19, %20, %21, %22, %23, %24, %25, %26, %27, %28, %29, %30, %31, %32, %33, %34, %35, %36, %37, %38, %39, %40, %41, %42, %43, %44, %45, %46, %47, %48, %49, %50, %51, %52, %53, %54, %55, %56, %57, %58, %59, %60, %61, %62, %63}, %64, %65, p, 1, 1, 0, %67;\n}\n"
        : "+f"(d[0]), "+f"(d[1]), "+f"(d[2]), "+f"(d[3]), "+f"(d[4]), "+f"(d[5]), "+f"(d[6]), "+f"(d[7]), "+f"(d[8]), "+f"(d[9]), "+f"(d[10]), "+f"(d[11]), "+f"(d[12]), "+f"(d[13]), "+f"(d[14]), "+f"(d[15]), "+f"(d[16]), "+f"(d[17]), "+f"(d[18]), "+f"(d[19]), "+f"(d[20]), "+f"(d[21]), "+f"(d[22]), "+f"(d[23]), "+f"(d[24]), "+f"(d[25]), "+f"(d[26]), "+f"(d[27]), "+f"(d[28]), "+f"(d[29]), "+f"(d[30]), "+f"(d[31]), "+f"(d[32]), "+f"(d[33]), "+f"(d[34]), "+f"(d[35]), "+f"(d[36]), "+f"(d[37]), "+f"(d[38]), "+f"(d[39]), "+f"(d[40]), "+f"(d[41]), "+f"(d[42]), "+f"(d[43]), "+f"(d[44]), "+f"(d[45]), "+f"(d[46]), "+f"(d[47]), "+f"(d[48]), "+f"(d[49]), "+f"(d[50]), "+f"(d[51]), "+f"(d[52]), "+f"(d[53]), "+f"(d[54]), "+f"(d[55]), "+f"(d[56]), "+f"(d[57]), "+f"(d[58]), "+f"(d[59]), "+f"(d[60]), "+f"(d[61]), "+f"(d[62]), "+f"(d[63])
        : "l"(da), "l"(db), "r"(scaleD), "n"(TB));
}
template <int TB>
__device__ __forceinline__ void wgmma_n224(float (&d)[112], uint64_t da, uint64_t db, int scaleD) {
    asm volatile("{\n.reg .pred p;\nsetp.ne.b32 p, %114, 0;\n"
        "wgmma.mma_async.sync.aligned.m64n224k16.f32.bf16.bf16 {%0, %1, %2, %3, %4, %5, %6, %7, %8, %9, %10, %11, %12, %13, %14, %15, %16, %17, %18, %19, %20, %21, %22, %23, %24, %25, %26, %27, %28, %29, %30, %31, %32, %33, %34, %35, %36, %37, %38, %39, %40, %41, %42, %43, %44, %45, %46, %47, %48, %49, %50, %51, %52, %53, %54, %55, %56, %57, %58, %59, %60, %61, %62, %63, %64, %65, %66, %67, %68, %69, %70, %71, %72, %73, %74, %75, %76, %77, %78, %79, %80, %81, %82, %83, %84, %85, %86, %87, %88, %89, %90, %91, %92, %93, %94, %95, %96, %97, %98, %99, %100, %101, %102, %103, %104, %105, %106, %107, %108, %109, %110, %111}, %112, %113, p, 1, 1, 0, %115;\n}\n"
        : "+f"(d[0]), "+f"(d[1]), "+f"(d[2]), "+f"(d[3]), "+f"(d[4]), "+f"(d[5]), "+f"(d[6]), "+f"(d[7]), "+f"(d[8]), "+f"(d[9]), "+f"(d[10]), "+f"(d[11]), "+f"(d[12]), "+f"(d[13]), "+f"(d[14]), "+f"(d[15]), "+f"(d[16]), "+f"(d[17]), "+f"(d[18]), "+f"(d[19]), "+f"(d[20]), "+f"(d[21]), "+f"(d[22]), "+f"(d[23]), "+f"(d[24]), "+f"(d[25]), "+f"(d[26]), "+f"(d[27]), "+f"(d[28]), "+f"(d[29]), "+f"(d[30]), "+f"(d[31]), "+f"(d[32]), "+f"(d[33]), "+f"(d[34]), "+f"(d[35]), "+f"(d[36]), "+f"(d[37]), "+f"(d[38]), "+f"(d[39]), "+f"(d[40]), "+f"(d[41]), "+f"(d[42]), "+f"(d[43]), "+f"(d[44]), "+f"(d[45]), "+f"(d[46]), "+f"(d[47]), "+f"(d[48]), "+f"(d[49]), "+f"(d[50]), "+f"(d[51]), "+f"(d[52]), "+f"(d[53]), "+f"(d[54]), "+f"(d[55]), "+f"(d[56]), "+f"(d[57]), "+f"(d[58]), "+f"(d[59]), "+f"(d[60]), "+f"(d[61]), "+f"(d[62]), "+f"(d[63]), "+f"(d[64]), "+f"(d[65]), "+f"(d[66]), "+f"(d[67]), "+f"(d[68]), "+f"(d[69]), "+f"(d[70]), "+f"(d[71]), "+f"(d[72]), "+f"(d[73]), "+f"(d[74]), "+f"(d[75]), "+f"(d[76]), "+f"(d[77]), "+f"(d[78]), "+f"(d[79]), "+f"(d[80]), "+f"(d[81]), "+f"(d[82]), "+f"(d[83]), "+f"(d[84]), "+f"(d[85]), "+f"(d[86]), "+f"(d[87]), "+f"(d[88]), "+f"(d[89]), "+f"(d[90]), "+f"(d[91]), "+f"(d[92]), "+f"(d[93]), "+f"(d[94]), "+f"(d[95]), "+f"(d[96]), "+f"(d[97]), "+f"(d[98]), "+f"(d[99]), "+f"(d[100]), "+f"(d[101]), "+f"(d[102]), "+f"(d[103]), "+f"(d[104]), "+f"(d[105]), "+f"(d[106]), "+f"(d[107]), "+f"(d[108]), "+f"(d[109]), "+f"(d[110]), "+f"(d[111])
        : "l"(da), "l"(db), "r"(scaleD), "n"(TB));
}

constexpr int S1_STAGES = 7;
constexpr int S1_XN = 0;
constexpr int S1_B = 7 * 16384;
constexpr int Y_STAGES = 5, Y_STAGE = 45056;
constexpr int F_STAGES = 4, F_STAGE = 49152;
constexpr int BAR = S1_B + S1_STAGES * 16384;
constexpr int BAR_F1 = BAR, BAR_E1 = BAR + 56, BAR_F2 = BAR + 112, BAR_E2 = BAR + 152, BAR_S1DONE = BAR + 192;
constexpr int BAR_PUB = BAR + 208;
constexpr int DEP_CNT = BAR + 200;
constexpr int SMEM_BYTES = BAR + 256 + 1024;
constexpr int TPITCH = 464;

__device__ __forceinline__ int n_passes(int j) { return j < 6 ? 3 : (j == 6 ? 9 : 8); }
__device__ __forceinline__ int pass_slab(int j, int p) {
    if (p == 0) return j < 7 ? -1 : 0;
    if (p < 3) return 8 * p - 7 + j;
    return 17 + 2 * (p - 3) + (j - 6);
}

template <int TB>
__device__ __forceinline__ void s1_mainloop(float (&acc)[2][64], uint32_t sb, int idx, int lane, int handoff) {
    int st = idx % S1_STAGES;
    uint32_t ph = (idx / S1_STAGES) & 1;
    int prev = 0;
    uint64_t da = mkdesc(sb + S1_XN, 16, 1024);
    const uint64_t db0 = TB ? mkdesc(sb + S1_B, 8192, 1024) : mkdesc(sb + S1_B, 16, 1024);
#pragma unroll 1
    for (int kb = 0; kb < 7; kb++) {
        mbar_wait(sb + BAR_F1 + 8 * st, ph);
        if (kb == 6 && handoff) asm volatile("bar.arrive %0, 256;" ::"r"(handoff) : "memory");
        const uint64_t db = db0 + st * 1024;
        wg_arrive();
#pragma unroll
        for (int s = 0; s < 4; s++) {
            wgmma_n128<TB>(acc[0], da + s * 2, db + s * (TB ? 128 : 2), kb | s);
            wgmma_n128<TB>(acc[1], da + 512 + s * 2, db + s * (TB ? 128 : 2), kb | s);
        }
        wg_commit();
        wg_wait<1>();
        if (kb > 0 && lane == 0) mbar_arrive_both(sb + BAR_E1 + 8 * prev);
        prev = st;
        da += 1024;
        if (++st == S1_STAGES) { st = 0; ph ^= 1; }
    }
    wg_wait<0>();
    if (lane == 0) mbar_arrive_both(sb + BAR_E1 + 8 * prev);
}

template <int TB>
__device__ __forceinline__ void s2_mainloop(float (&acc)[112], uint32_t sb, int wg, int lane) {
    constexpr int NST = TB ? F_STAGES : Y_STAGES, SSZ = TB ? F_STAGE : Y_STAGE, NKB = TB ? 28 : 32;
    int st = 0;
    uint32_t ph = 0;
    int prev = 0;
    const uint64_t da0 = mkdesc(sb + wg * 8192, 16, 1024);
    const uint64_t db0 = TB ? mkdesc(sb + 16384, 8192, 1024) : mkdesc(sb + 16384, 16, 1024);
#pragma unroll 1
    for (int i = 0; i < NKB; i++) {
        mbar_wait(sb + BAR_F2 + 8 * st, ph);
        const uint64_t da = da0 + st * (SSZ / 16), db = db0 + st * (SSZ / 16);
        wg_arrive();
#pragma unroll
        for (int s = 0; s < 4; s++) wgmma_n224<TB>(acc, da + s * 2, db + s * (TB ? 128 : 2), i | s);
        wg_commit();
        wg_wait<1>();
        if (i > 0 && lane == 0) mbar_arrive_both(sb + BAR_E2 + 8 * prev);
        prev = st;
        if (++st == NST) { st = 0; ph ^= 1; }
    }
    wg_wait<0>();
}

struct Maps {
    CUtensorMap wg, wu, hre, him, h, abT, sre, sim, wd;
};
struct Ptrs {
    const __nv_bfloat16 *x, *hre, *him, *wg, *wu, *wd;
    __nv_bfloat16* out;
};
__device__ __forceinline__ void mbar_arrive(uint32_t b) {
    asm volatile("mbarrier.arrive.shared::cta.b64 _, [%0];" ::"r"(b) : "memory");
}
__device__ __forceinline__ void l2_prefetch(const void* p, uint32_t bytes) {
    asm volatile("cp.async.bulk.prefetch.L2.global [%0], %1;" ::"l"(p), "r"(bytes) : "memory");
}
__device__ __forceinline__ void tma_prefetch(const CUtensorMap* m, int c0, int c1) {
    asm volatile("cp.async.bulk.prefetch.tensor.2d.L2.global.tile [%0, {%1, %2}];" ::"l"(m), "r"(c0), "r"(c1) : "memory");
}

__device__ __forceinline__ void dep_wait(uint32_t sb, uint32_t need) {
    uint32_t v;
    do { asm volatile("ld.acquire.cta.shared.u32 %0, [%1];" : "=r"(v) : "r"(sb + DEP_CNT) : "memory"); } while (v < need);
}

__global__ void __launch_bounds__(384, 1)
fused_kernel(const __grid_constant__ Ptrs pt, const __grid_constant__ Maps tm) {
    extern __shared__ unsigned char smem_raw[];
    const uint32_t sb = (s2u(smem_raw) + 1023) & ~1023u;
    const int tid = threadIdx.x, lane = tid & 31;
    const int warp = __shfl_sync(0xffffffffu, tid >> 5, 0);
    const int rank = blockIdx.x & 1;
    const int cid = blockIdx.x >> 1;
    const int j = cid & 7;
    const int rb = (cid >> 3) * 2 + rank;
    const int npass = n_passes(j);
    const int n = j & 1;
    const int part = j >> 1;

    {
        const int l8 = lane & 7, sub = lane >> 3;
        uint4 v[3][7];
#pragma unroll
        for (int it = 0; it < 3; it++) {
            const int qd = warp + 12 * it;
            if (qd < 32) {
                const uint4* src = reinterpret_cast<const uint4*>(pt.x + (size_t)(rb * 128 + qd * 4 + sub) * D_) + l8;
#pragma unroll
                for (int i = 0; i < 7; i++) v[it][i] = __ldg(src + i * 8);
            }
        }
        if (tid == 256) {
            TL(0, 0);
            for (int i = 0; i < S1_STAGES; i++) { mbar_init(sb + BAR_F1 + 8 * i, 1); mbar_init(sb + BAR_E1 + 8 * i, 8); }
            for (int i = 0; i < Y_STAGES; i++) { mbar_init(sb + BAR_F2 + 8 * i, 1); mbar_init(sb + BAR_E2 + 8 * i, 16); }
            mbar_init(sb + BAR_S1DONE, 16);
            mbar_init(sb + BAR_PUB, 4);
            mbar_init(sb + BAR_PUB + 8, 4);
            asm volatile("st.shared.u32 [%0], %1;" ::"r"(sb + DEP_CNT), "r"(0) : "memory");
            asm volatile("fence.mbarrier_init.release.cluster;" ::: "memory");
        }
        __syncwarp();
        asm volatile("barrier.cluster.arrive.relaxed.aligned;\nbarrier.cluster.wait.aligned;" ::: "memory");
        if (tid == 256) {
            const int slab = pass_slab(j, 0);
            for (int kb = 0; kb < 7; kb++) {
                const uint32_t dst = sb + S1_B + kb * 16384 + rank * 8192;
                const uint32_t fb = sb + BAR_F1 + 8 * kb;
                mbar_expect(fb, 16384);
                if (slab >= 0) {
                    tma_load_mc(dst, rank ? &tm.wu : &tm.wg, fb, slab * 64, kb * 64);
                } else {
                    const int a = 2 * j + rank;
                    tma_load_mc(dst, a < 7 ? &tm.hre : &tm.him, fb, kb * 64, (a < 7 ? a : a - 7) * 64);
                }
            }
            const int b = blockIdx.x;
            l2_prefetch((const char*)pt.wg + b * 12544, 12544);
            l2_prefetch((const char*)pt.wu + b * 12544, 12544);
            l2_prefetch((const char*)pt.wd + b * 12544, 12544);
        }
        __syncwarp();
        if (tid == 0) TL(0, 1);
#pragma unroll
        for (int it = 0; it < 3; it++) {
            const int qd = warp + 12 * it;
            if (qd < 32) {
                const int row = qd * 4 + sub;
                float s0 = 0.f, s1 = 0.f;
#pragma unroll
                for (int i = 0; i < 7; i++) {
                    s0 += (bf_lo(v[it][i].x) + bf_hi(v[it][i].x)) + (bf_lo(v[it][i].y) + bf_hi(v[it][i].y));
                    s1 += (bf_lo(v[it][i].z) + bf_hi(v[it][i].z)) + (bf_lo(v[it][i].w) + bf_hi(v[it][i].w));
                }
                float s = s0 + s1;
                s += __shfl_xor_sync(0xffffffffu, s, 1);
                s += __shfl_xor_sync(0xffffffffu, s, 2);
                s += __shfl_xor_sync(0xffffffffu, s, 4);
                if (it == 0 && tid == 0) TL(0, 3);
                const float mean = s * (1.0f / D_);
                float q0 = 0.f, q1 = 0.f;
#pragma unroll
                for (int i = 0; i < 7; i++) {
                    const uint32_t w[4] = {v[it][i].x, v[it][i].y, v[it][i].z, v[it][i].w};
#pragma unroll
                    for (int c = 0; c < 4; c++) {
                        const float d0 = bf_lo(w[c]) - mean, d1 = bf_hi(w[c]) - mean;
                        q0 = fmaf(d0, d0, q0);
                        q1 = fmaf(d1, d1, q1);
                    }
                }
                float q = q0 + q1;
                q += __shfl_xor_sync(0xffffffffu, q, 1);
                q += __shfl_xor_sync(0xffffffffu, q, 2);
                q += __shfl_xor_sync(0xffffffffu, q, 4);
                const float var = rbf(q * (1.0f / D_));
                const float den = rbf(sqrtf(rbf(var + 1e-5f)));
                const float rinv = 1.0f / den;
                const float rhi = rbf(rinv);
                const uint32_t m2 = pack_bf16(mean, mean), rhi2 = pack_bf16(rhi, rhi), rlo2 = pack_bf16(rinv - rhi, rinv - rhi);
                const uint32_t dst = sb + S1_XN + row * 128 + ((l8 ^ (row & 7)) << 4);
#pragma unroll
                for (int i = 0; i < 7; i++) {
                    const uint32_t w[4] = {v[it][i].x, v[it][i].y, v[it][i].z, v[it][i].w};
                    uint32_t o[4];
#pragma unroll
                    for (int c = 0; c < 4; c++) {
                        const uint32_t xc = hsub2(w[c], m2);
                        o[c] = hfma2(xc, rhi2, hmul2(xc, rlo2));
                    }
                    asm volatile("st.shared.v4.b32 [%0], {%1, %2, %3, %4};" ::"r"(dst + i * 16384), "r"(o[0]), "r"(o[1]), "r"(o[2]), "r"(o[3]) : "memory");
                }
            }
        }
        fence_async();
        __syncthreads();
        if (tid == 0) TL(0, 2);
    }

    if (warp >= 8) {
        asm volatile("setmaxnreg.dec.sync.aligned.u32 40;");
        if (warp == 8) {
            if (lane == 0) {
                int st = 0;
                uint32_t ph = 0;
                for (int p = 1; p < npass; p++) {
                    const int slab = pass_slab(j, p);
                    for (int kb = 0; kb < 7; kb++) {
                        mbar_wait(sb + BAR_E1 + 8 * st, ph);
                        const uint32_t fb = sb + BAR_F1 + 8 * st;
                        mbar_expect(fb, 16384);
                        tma_load_mc(sb + S1_B + st * 16384 + rank * 8192, rank ? &tm.wu : &tm.wg, fb, slab * 64, kb * 64);
                        if (++st == S1_STAGES) { st = 0; ph ^= 1; }
                    }
                }
                if (part < 3) {
                    mbar_wait(sb + BAR_S1DONE, 0);
                    TL(0, 24);
                    st = 0; ph = 1;
                    if (part < 2) {
                        const CUtensorMap* ma = part ? &tm.sim : &tm.sre;
                        for (int g = 0; g < 32; g++) {
                            mbar_wait(sb + BAR_E2 + 8 * st, ph);
                            const uint32_t dst = sb + st * Y_STAGE;
                            const uint32_t fb = sb + BAR_F2 + 8 * st;
                            mbar_expect(fb, Y_STAGE);
                            tma_load(dst, ma, fb, g * 64, rb * 128);
                            dep_wait(sb, (g >> 1) + 1);
                            tma_load_mc(dst + 16384 + rank * 14336, &tm.abT, fb, g * 64, part * 448 + n * 224 + rank * 112);
                            if (++st == Y_STAGES) { st = 0; ph ^= 1; }
                        }
                    } else {
                        for (int g = 0; g < 28; g++) {
                            mbar_wait(sb + BAR_E2 + 8 * st, ph);
                            const uint32_t dst = sb + st * F_STAGE;
                            const uint32_t fb = sb + BAR_F2 + 8 * st;
                            mbar_expect(fb, F_STAGE);
                            tma_load_mc(dst + 16384 + (2 * rank) * 8192, &tm.wd, fb, n * 224 + (2 * rank) * 64, g * 64);
                            tma_load_mc(dst + 16384 + (2 * rank + 1) * 8192, &tm.wd, fb, n * 224 + (2 * rank + 1) * 64, g * 64);
                            dep_wait(sb, g + 1);
                            tma_load(dst, &tm.h, fb, g * 64, rb * 128);
                            if (++st == F_STAGES) { st = 0; ph ^= 1; }
                        }
                    }
                }
            }
        } else if (warp == 9) {
            if (part < 3) {
                if (part < 2 && lane < 16) {
                    tma_prefetch(part ? &tm.sim : &tm.sre, (2 * lane + n) * 64, rb * 128);
                }
                const int ndep = part < 2 ? 16 : 29;
                const unsigned int epoch = *(volatile unsigned int*)&g_fl.done / gridDim.x + 1;
                const unsigned int* f = part < 2 ? &g_fl.ab[lane & 15] : (lane < 28 ? &g_fl.h[rb * 28 + lane] : &g_fl.y[rb * 2 + n]);
                const unsigned int target = (part < 2 ? 7 : (lane < 28 ? 1 : 16)) * epoch;
                bool ok = lane >= ndep;
                int published = 0;
                for (int spins = 0; published < ndep && spins < (1 << 22); spins++) {
                    if (!ok) {
                        unsigned int v;
                        asm volatile("ld.acquire.gpu.global.u32 %0, [%1];" : "=r"(v) : "l"(f) : "memory");
                        ok = (int)(v - target) >= 0;
                    }
                    const unsigned int m = __ballot_sync(0xffffffffu, ok);
                    const int cnt = min(__ffs(~m) - 1, ndep);
                    if (m == 0xffffffffu || cnt > published) {
                        published = (m == 0xffffffffu) ? ndep : cnt;
                        fence_async_all();
                        __syncwarp();
                        if (lane == 0) asm volatile("st.release.cta.shared.u32 [%0], %1;" ::"r"(sb + DEP_CNT), "r"(published) : "memory");
                    }
                }
                if (published < ndep && lane == 0)
                    asm volatile("st.release.cta.shared.u32 [%0], %1;" ::"r"(sb + DEP_CNT), "r"(ndep) : "memory");
            }
        } else {
            if (lane == 0) {
                const int w = warp - 10;
                uint32_t ph = 0;
                for (int p = w; p < npass; p += 2) {
                    const int slab = pass_slab(j, p);
                    mbar_wait(sb + BAR_PUB + 8 * w, ph);
                    ph ^= 1;
                    __threadfence();
                    flag_add(slab >= 0 ? &g_fl.h[rb * 28 + slab] : &g_fl.ab[rb]);
                }
            }
        }
        __syncwarp();
    } else {
        asm volatile("setmaxnreg.inc.sync.aligned.u32 232;");
        const int wg = warp >> 2, wl = warp & 3, wtid = tid & 127;
        const int qd = lane & 3;
        {
            float acc[2][64];
            for (int p = wg; p < npass; p += 2) {
                const int slab = pass_slab(j, p);
                if (p > 0) bar_sync(4 + (p & 1), 256);
                const int handoff = (p + 1 < npass) ? 4 + ((p + 1) & 1) : 0;
                if (slab >= 0) s1_mainloop<1>(acc, sb, p * 7, lane, handoff);
                else s1_mainloop<0>(acc, sb, p * 7, lane, handoff);
                if (p + 2 >= npass && lane == 0) mbar_arrive_both(sb + BAR_S1DONE);
                if (wtid == 0 && p < 4) TL(0, 4 + p);

                if (slab >= 0) {
                    __nv_bfloat16* dst = g_h + (size_t)(rb * 128 + wl * 16 + (lane >> 2)) * F_ + slab * 64 + qd * 8;
#pragma unroll
                    for (int mh = 0; mh < 2; mh++) {
#pragma unroll
                        for (int hh = 0; hh < 2; hh++) {
#pragma unroll
                            for (int g4 = 0; g4 < 2; g4++) {
                                uint32_t r[4];
#pragma unroll
                                for (int t = 0; t < 4; t++) {
                                    const int o = (g4 * 4 + t) * 4 + hh * 2;
                                    const uint32_t g2 = pack_bf16(acc[mh][o], acc[mh][o + 1]);
                                    const uint32_t u2 = pack_bf16(acc[mh][32 + o], acc[mh][32 + o + 1]);
                                    const uint32_t a2 = pack_bf16(gelu_tanh(bf_lo(g2)), gelu_tanh(bf_hi(g2)));
                                    r[t] = hmul2(a2, u2);
                                }
                                quad_transpose(r, qd);
                                __stcg(reinterpret_cast<uint4*>(dst + (size_t)(mh * 64 + hh * 8) * F_ + g4 * 32), make_uint4(r[0], r[1], r[2], r[3]));
                            }
                        }
                    }
                } else {
                    __nv_bfloat16* dst = g_abT + (size_t)(j * 128 + (qd >> 1) * 8 + (lane >> 2)) * S_ + rb * 128 + wl * 16 + (qd & 1) * 8;
#pragma unroll
                    for (int mh = 0; mh < 2; mh++) {
#pragma unroll
                        for (int jj = 0; jj < 16; jj += 2) {
                            uint32_t r[4];
#pragma unroll
                            for (int t = 0; t < 4; t++) {
                                const int o = (jj + (t >> 1)) * 4 + (t & 1) * 2;
                                r[t] = movmat_t(pack_bf16(acc[mh][o], acc[mh][o + 1]));
                            }
                            quad_transpose(r, qd);
                            __stcg(reinterpret_cast<uint4*>(dst + (size_t)(jj * 8) * S_ + mh * 64), make_uint4(r[0], r[1], r[2], r[3]));
                        }
                    }
                }
                __syncwarp();
                if (lane == 0) mbar_arrive(sb + BAR_PUB + 8 * wg);
                if (wtid == 0 && p < 4) TL(0, 10 + p);
            }
        }
        if (wtid == 0) TL(0, 20 + wg);
        if (part < 3) {
            {
                float acc[112];
                const size_t base = (size_t)(rb * 128 + wg * 64 + wl * 16 + (lane >> 2)) * D_ + n * 224 + qd * 8;
                if (part < 2) {
                    s2_mainloop<0>(acc, sb, wg, lane);
                    if (tid == 0) TL(0, 25);
                    __nv_bfloat16* dst = g_y + (size_t)part * S_ * D_ + base;
#pragma unroll
                    for (int hh = 0; hh < 2; hh++) {
#pragma unroll
                        for (int g4 = 0; g4 < 7; g4++) {
                            uint32_t r[4];
#pragma unroll
                            for (int t = 0; t < 4; t++) r[t] = pack_bf16(acc[(g4 * 4 + t) * 4 + hh * 2], acc[(g4 * 4 + t) * 4 + hh * 2 + 1]);
                            quad_transpose(r, qd);
                            __stcg(reinterpret_cast<uint4*>(dst + (size_t)(hh * 8) * D_ + g4 * 32), make_uint4(r[0], r[1], r[2], r[3]));
                        }
                    }
                    __threadfence();
                    __syncwarp();
                    if (lane == 0) flag_add(&g_fl.y[rb * 2 + n]);
                } else {
                    uint4 xv[14];
#pragma unroll
                    for (int i = 0; i < 14; i++)
                        xv[i] = __ldg(reinterpret_cast<const uint4*>(pt.x + base + (i / 7) * 8 * D_ + (i % 7) * 32));
                    s2_mainloop<1>(acc, sb, wg, lane);
                    if (tid == 0) TL(0, 25);
                    dep_wait(sb, 29);
                    if (tid == 0) TL(0, 26);
                    uint32_t gq[56];
#pragma unroll
                    for (int hh = 0; hh < 2; hh++) {
                        uint4 yr[7], yi[7];
#pragma unroll
                        for (int i = 0; i < 7; i++) {
                            yr[i] = __ldcg(reinterpret_cast<const uint4*>(g_y + base + hh * 8 * D_ + i * 32));
                            yi[i] = __ldcg(reinterpret_cast<const uint4*>(g_y + (size_t)S_ * D_ + base + hh * 8 * D_ + i * 32));
                        }
                        if (hh == 0) {
#pragma unroll
                            for (int i = 0; i < 56; i++) {
                                const uint32_t f2 = pack_bf16(acc[2 * i], acc[2 * i + 1]);
                                gq[i] = pack_bf16(silu(bf_lo(f2)), silu(bf_hi(f2)));
                            }
                        }
#pragma unroll
                        for (int g4 = 0; g4 < 7; g4++) {
                            uint32_t r[4];
#pragma unroll
                            for (int t = 0; t < 4; t++) r[t] = gq[(g4 * 4 + t) * 2 + hh];
                            quad_transpose(r, qd);
                            const uint4 xx = xv[hh * 7 + g4];
                            uint4 o;
                            o.x = hadd2(xx.x, hmul2(hsub2(yr[g4].x, yi[g4].x), r[0]));
                            o.y = hadd2(xx.y, hmul2(hsub2(yr[g4].y, yi[g4].y), r[1]));
                            o.z = hadd2(xx.z, hmul2(hsub2(yr[g4].z, yi[g4].z), r[2]));
                            o.w = hadd2(xx.w, hmul2(hsub2(yr[g4].w, yi[g4].w), r[3]));
                            *reinterpret_cast<uint4*>(pt.out + base + hh * 8 * D_ + g4 * 32) = o;
                        }
                    }
                }
            }
        }
    }
    if (tid == 0) TL(0, 29);
    cluster_sync();
    if (tid == 0) {
        TL(0, 30);
        atomicAdd(&g_fl.done, 1u);
    }
}

typedef CUresult (*EncFn)(CUtensorMap*, CUtensorMapDataType, cuuint32_t, void*, const cuuint64_t*, const cuuint64_t*,
                          const cuuint32_t*, const cuuint32_t*, CUtensorMapInterleave, CUtensorMapSwizzle,
                          CUtensorMapL2promotion, CUtensorMapFloatOOBfill);

void make_map(EncFn enc, CUtensorMap* m, const void* ptr, int rows, int cols, int box_rows, int box_cols, bool swz = true) {
    cuuint64_t gd[2] = {(cuuint64_t)cols, (cuuint64_t)rows};
    cuuint64_t gs[1] = {(cuuint64_t)cols * 2};
    cuuint32_t bx[2] = {(cuuint32_t)box_cols, (cuuint32_t)box_rows};
    cuuint32_t es[2] = {1, 1};
    enc(m, CU_TENSOR_MAP_DATA_TYPE_BFLOAT16, 2, const_cast<void*>(ptr), gd, gs, bx, es, CU_TENSOR_MAP_INTERLEAVE_NONE,
        swz ? CU_TENSOR_MAP_SWIZZLE_128B : CU_TENSOR_MAP_SWIZZLE_NONE, CU_TENSOR_MAP_L2_PROMOTION_L2_128B,
        CU_TENSOR_MAP_FLOAT_OOB_FILL_NONE);
}

}

extern "C" void kernel_launch(void* const* d_in, const int* in_sizes, int n_in, void* d_out, int out_size) {
    Ptrs pt;
    pt.x = (const __nv_bfloat16*)d_in[0];
    pt.hre = (const __nv_bfloat16*)d_in[3];
    pt.him = (const __nv_bfloat16*)d_in[4];
    pt.wg = (const __nv_bfloat16*)d_in[6];
    pt.wu = (const __nv_bfloat16*)d_in[7];
    pt.wd = (const __nv_bfloat16*)d_in[8];
    pt.out = (__nv_bfloat16*)d_out;

    void* fn = nullptr;
    cudaDriverEntryPointQueryResult qr;
    cudaGetDriverEntryPoint("cuTensorMapEncodeTiled", &fn, cudaEnableDefault, &qr);
    EncFn enc = (EncFn)fn;
    void *p_abT, *p_h;
    cudaGetSymbolAddress(&p_abT, g_abT);
    cudaGetSymbolAddress(&p_h, g_h);

    Maps tm;
    make_map(enc, &tm.wg, d_in[6], D_, F_, 64, 64);
    make_map(enc, &tm.wu, d_in[7], D_, F_, 64, 64);
    make_map(enc, &tm.hre, d_in[3], D_, D_, 64, 64);
    make_map(enc, &tm.him, d_in[4], D_, D_, 64, 64);
    make_map(enc, &tm.h, p_h, S_, F_, 128, 64);
    make_map(enc, &tm.abT, p_abT, 896, S_, 112, 64);
    make_map(enc, &tm.sre, d_in[1], S_, S_, 128, 64);
    make_map(enc, &tm.sim, d_in[2], S_, S_, 128, 64);
    make_map(enc, &tm.wd, d_in[8], F_, D_, 64, 64);

    cudaFuncSetAttribute(fused_kernel, cudaFuncAttributeMaxDynamicSharedMemorySize, SMEM_BYTES);

    cudaLaunchAttribute at[1];
    at[0].id = cudaLaunchAttributeClusterDimension;
    at[0].val.clusterDim.x = 2; at[0].val.clusterDim.y = 1; at[0].val.clusterDim.z = 1;
    cudaLaunchConfig_t cfg = {};
    cfg.gridDim = dim3(128); cfg.blockDim = dim3(384); cfg.stream = cudaStreamPerThread;
    cfg.attrs = at; cfg.numAttrs = 1;
    cfg.dynamicSmemBytes = SMEM_BYTES;
    cudaLaunchKernelEx(&cfg, fused_kernel, pt, tm);
}
```

```cpp
#include <cuda_runtime.h>
#include <cuda_bf16.h>
#include <cuda.h>
#include <stdint.h>

namespace {

constexpr int S_ = 2048, D_ = 448, F_ = 1792;

constexpr int ABP = 2048 + 64;
__device__ __align__(1024) __nv_bfloat16 g_abT[896 * ABP];
__device__ __align__(1024) __nv_bfloat16 g_h[2048 * 1792];
__device__ __align__(1024) uint4 g_y[2 * 32 * 14 * 256];
struct Flags {
    unsigned int ab[16];
    unsigned int h[16 * 28];
    unsigned int y[32];
    unsigned int done;
};
__device__ Flags g_fl;

#define TL(k, i) do {} while (0)
__device__ __forceinline__ uint32_t s2u(const void* p) { return (uint32_t)__cvta_generic_to_shared(p); }
__device__ __forceinline__ void mbar_init(uint32_t b, int c) {
    asm volatile("mbarrier.init.shared::cta.b64 [%0], %1;" ::"r"(b), "r"(c));
}
__device__ __forceinline__ void mbar_expect(uint32_t b, uint32_t bytes) {
    asm volatile("mbarrier.arrive.expect_tx.shared::cta.b64 _, [%0], %1;" ::"r"(b), "r"(bytes) : "memory");
}
__device__ __forceinline__ void mbar_wait(uint32_t b, uint32_t ph) {
    uint32_t ok;
    do {
        asm volatile("{\n.reg .pred p;\nmbarrier.try_wait.parity.shared::cta.b64 p, [%1], %2;\nselp.u32 %0, 1, 0, p;\n}"
                     : "=r"(ok) : "r"(b), "r"(ph) : "memory");
    } while (!ok);
}
__device__ __forceinline__ void mbar_arrive_both(uint32_t b) {
    asm volatile("{\n.reg .b32 r0, r1;\n"
                 "mapa.shared::cluster.u32 r0, %0, 0;\n"
                 "mapa.shared::cluster.u32 r1, %0, 1;\n"
                 "mbarrier.arrive.shared::cluster.b64 _, [r0];\n"
                 "mbarrier.arrive.shared::cluster.b64 _, [r1];\n}"
                 ::"r"(b) : "memory");
}
__device__ __forceinline__ void tma_load(uint32_t dst, const CUtensorMap* m, uint32_t bar, int c0, int c1) {
    asm volatile("cp.async.bulk.tensor.2d.shared::cluster.global.mbarrier::complete_tx::bytes [%0], [%1, {%3, %4}], [%2];"
                 ::"r"(dst), "l"(m), "r"(bar), "r"(c0), "r"(c1) : "memory");
}
__device__ __forceinline__ void tma_load_mc(uint32_t dst, const CUtensorMap* m, uint32_t bar, int c0, int c1) {
    asm volatile("cp.async.bulk.tensor.2d.shared::cluster.global.mbarrier::complete_tx::bytes.multicast::cluster [%0], [%1, {%3, %4}], [%2], %5;"
                 ::"r"(dst), "l"(m), "r"(bar), "r"(c0), "r"(c1), "h"((uint16_t)3) : "memory");
}
__device__ __forceinline__ void tma_store(const CUtensorMap* m, uint32_t src, int c0, int c1) {
    asm volatile("cp.async.bulk.tensor.2d.global.shared::cta.bulk_group [%0, {%2, %3}], [%1];"
                 ::"l"(m), "r"(src), "r"(c0), "r"(c1) : "memory");
}
__device__ __forceinline__ void bulk_commit() { asm volatile("cp.async.bulk.commit_group;" ::: "memory"); }
__device__ __forceinline__ void bulk_wait_read0() { asm volatile("cp.async.bulk.wait_group.read 0;" ::: "memory"); }
__device__ __forceinline__ void bulk_wait0() { asm volatile("cp.async.bulk.wait_group 0;" ::: "memory"); }
__device__ __forceinline__ void fence_async() { asm volatile("fence.proxy.async.shared::cta;" ::: "memory"); }
__device__ __forceinline__ void fence_async_all() { asm volatile("fence.proxy.async;" ::: "memory"); }
__device__ __forceinline__ void cluster_sync() {
    asm volatile("barrier.cluster.arrive.release.aligned;\nbarrier.cluster.wait.acquire.aligned;" ::: "memory");
}
__device__ __forceinline__ void bar_sync(int id, int n) { asm volatile("bar.sync %0, %1;" ::"r"(id), "r"(n) : "memory"); }
__device__ __forceinline__ void wg_arrive() { asm volatile("wgmma.fence.sync.aligned;" ::: "memory"); }
__device__ __forceinline__ void wg_commit() { asm volatile("wgmma.commit_group.sync.aligned;" ::: "memory"); }
template <int N> __device__ __forceinline__ void wg_wait() { asm volatile("wgmma.wait_group.sync.aligned %0;" ::"n"(N) : "memory"); }
__device__ __forceinline__ void stmat4(uint32_t a, uint32_t r0, uint32_t r1, uint32_t r2, uint32_t r3) {
    asm volatile("stmatrix.sync.aligned.m8n8.x4.shared.b16 [%0], {%1, %2, %3, %4};" ::"r"(a), "r"(r0), "r"(r1), "r"(r2), "r"(r3) : "memory");
}
__device__ __forceinline__ void stmat4t(uint32_t a, uint32_t r0, uint32_t r1, uint32_t r2, uint32_t r3) {
    asm volatile("stmatrix.sync.aligned.m8n8.x4.trans.shared.b16 [%0], {%1, %2, %3, %4};" ::"r"(a), "r"(r0), "r"(r1), "r"(r2), "r"(r3) : "memory");
}
__device__ __forceinline__ void ldmat4(uint32_t a, uint32_t (&r)[4]) {
    asm volatile("ldmatrix.sync.aligned.m8n8.x4.shared.b16 {%0, %1, %2, %3}, [%4];"
                 : "=r"(r[0]), "=r"(r[1]), "=r"(r[2]), "=r"(r[3]) : "r"(a) : "memory");
}
__device__ __forceinline__ void flag_add(unsigned int* f) {
    asm volatile("red.release.gpu.global.add.u32 [%0], 1;" ::"l"(f) : "memory");
}
__device__ __forceinline__ void flag_wait(const unsigned int* f, unsigned int target) {
    unsigned int v;
    int spins = 0;
    while (true) {
        asm volatile("ld.acquire.gpu.global.u32 %0, [%1];" : "=r"(v) : "l"(f) : "memory");
        if ((int)(v - target) >= 0 || ++spins > (1 << 22)) break;
    }
}
__device__ __forceinline__ void quad_transpose(uint32_t (&r)[4], int q) {
    const bool o1 = q & 1, o2 = q & 2;
    uint32_t a = o1 ? r[0] : r[1], b = o1 ? r[2] : r[3];
    a = __shfl_xor_sync(0xffffffffu, a, 1);
    b = __shfl_xor_sync(0xffffffffu, b, 1);
    if (o1) { r[0] = a; r[2] = b; } else { r[1] = a; r[3] = b; }
    a = o2 ? r[0] : r[2]; b = o2 ? r[1] : r[3];
    a = __shfl_xor_sync(0xffffffffu, a, 2);
    b = __shfl_xor_sync(0xffffffffu, b, 2);
    if (o2) { r[0] = a; r[1] = b; } else { r[2] = a; r[3] = b; }
}
__device__ __forceinline__ uint32_t movmat_t(uint32_t v) {
    uint32_t r;
    asm volatile("movmatrix.sync.aligned.m8n8.trans.b16 %0, %1;" : "=r"(r) : "r"(v));
    return r;
}
__device__ __forceinline__ uint64_t mkdesc(uint32_t addr, uint32_t lbo, uint32_t sbo) {
    return (uint64_t)((addr & 0x3FFFF) >> 4) | ((uint64_t)(lbo >> 4) << 16) | ((uint64_t)(sbo >> 4) << 32) | (1ull << 62);
}
__device__ __forceinline__ uint32_t pack_bf16(float lo, float hi) {
    uint32_t r;
    asm("cvt.rn.bf16x2.f32 %0, %1, %2;" : "=r"(r) : "f"(hi), "f"(lo));
    return r;
}
__device__ __forceinline__ uint32_t hsub2(uint32_t a, uint32_t b) { uint32_t r; asm("sub.rn.bf16x2 %0, %1, %2;" : "=r"(r) : "r"(a), "r"(b)); return r; }
__device__ __forceinline__ uint32_t hadd2(uint32_t a, uint32_t b) { uint32_t r; asm("add.rn.bf16x2 %0, %1, %2;" : "=r"(r) : "r"(a), "r"(b)); return r; }
__device__ __forceinline__ uint32_t hmul2(uint32_t a, uint32_t b) { uint32_t r; asm("mul.rn.bf16x2 %0, %1, %2;" : "=r"(r) : "r"(a), "r"(b)); return r; }
__device__ __forceinline__ uint32_t hfma2(uint32_t a, uint32_t b, uint32_t c) { uint32_t r; asm("fma.rn.bf16x2 %0, %1, %2, %3;" : "=r"(r) : "r"(a), "r"(b), "r"(c)); return r; }
__device__ __forceinline__ float bf_lo(uint32_t u) { return __uint_as_float(u << 16); }
__device__ __forceinline__ float bf_hi(uint32_t u) { return __uint_as_float(u & 0xffff0000u); }
__device__ __forceinline__ float rbf(float v) { return __bfloat162float(__float2bfloat16_rn(v)); }
__device__ __forceinline__ float tanh_fast(float x) { float r; asm("tanh.approx.f32 %0, %1;" : "=f"(r) : "f"(x)); return r; }
__device__ __forceinline__ float gelu_tanh(float x) {
    float u = x * fmaf(x * x, 0.0356774081f, 0.7978845608f);
    float hx = 0.5f * x;
    return fmaf(hx, tanh_fast(u), hx);
}
__device__ __forceinline__ float silu(float f) { const float hf = 0.5f * f; return fmaf(hf, tanh_fast(hf), hf); }

template <int TB>
__device__ __forceinline__ void wgmma_n128(float (&d)[64], uint64_t da, uint64_t db, int scaleD) {
    asm volatile("{\n.reg .pred p;\nsetp.ne.b32 p, %66, 0;\n"
        "wgmma.mma_async.sync.aligned.m64n128k16.f32.bf16.bf16 {%0, %1, %2, %3, %4, %5, %6, %7, %8, %9, %10, %11, %12, %13, %14, %15, %16, %17, %18, %19, %20, %21, %22, %23, %24, %25, %26, %27, %28, %29, %30, %31, %32, %33, %34, %35, %36, %37, %38, %39, %40, %41, %42, %43, %44, %45, %46, %47, %48, %49, %50, %51, %52, %53, %54, %55, %56, %57, %58, %59, %60, %61, %62, %63}, %64, %65, p, 1, 1, 0, %67;\n}\n"
        : "+f"(d[0]), "+f"(d[1]), "+f"(d[2]), "+f"(d[3]), "+f"(d[4]), "+f"(d[5]), "+f"(d[6]), "+f"(d[7]), "+f"(d[8]), "+f"(d[9]), "+f"(d[10]), "+f"(d[11]), "+f"(d[12]), "+f"(d[13]), "+f"(d[14]), "+f"(d[15]), "+f"(d[16]), "+f"(d[17]), "+f"(d[18]), "+f"(d[19]), "+f"(d[20]), "+f"(d[21]), "+f"(d[22]), "+f"(d[23]), "+f"(d[24]), "+f"(d[25]), "+f"(d[26]), "+f"(d[27]), "+f"(d[28]), "+f"(d[29]), "+f"(d[30]), "+f"(d[31]), "+f"(d[32]), "+f"(d[33]), "+f"(d[34]), "+f"(d[35]), "+f"(d[36]), "+f"(d[37]), "+f"(d[38]), "+f"(d[39]), "+f"(d[40]), "+f"(d[41]), "+f"(d[42]), "+f"(d[43]), "+f"(d[44]), "+f"(d[45]), "+f"(d[46]), "+f"(d[47]), "+f"(d[48]), "+f"(d[49]), "+f"(d[50]), "+f"(d[51]), "+f"(d[52]), "+f"(d[53]), "+f"(d[54]), "+f"(d[55]), "+f"(d[56]), "+f"(d[57]), "+f"(d[58]), "+f"(d[59]), "+f"(d[60]), "+f"(d[61]), "+f"(d[62]), "+f"(d[63])
        : "l"(da), "l"(db), "r"(scaleD), "n"(TB));
}
template <int TB>
__device__ __forceinline__ void wgmma_n224(float (&d)[112], uint64_t da, uint64_t db, int scaleD) {
    asm volatile("{\n.reg .pred p;\nsetp.ne.b32 p, %114, 0;\n"
        "wgmma.mma_async.sync.aligned.m64n224k16.f32.bf16.bf16 {%0, %1, %2, %3, %4, %5, %6, %7, %8, %9, %10, %11, %12, %13, %14, %15, %16, %17, %18, %19, %20, %21, %22, %23, %24, %25, %26, %27, %28, %29, %30, %31, %32, %33, %34, %35, %36, %37, %38, %39, %40, %41, %42, %43, %44, %45, %46, %47, %48, %49, %50, %51, %52, %53, %54, %55, %56, %57, %58, %59, %60, %61, %62, %63, %64, %65, %66, %67, %68, %69, %70, %71, %72, %73, %74, %75, %76, %77, %78, %79, %80, %81, %82, %83, %84, %85, %86, %87, %88, %89, %90, %91, %92, %93, %94, %95, %96, %97, %98, %99, %100, %101, %102, %103, %104, %105, %106, %107, %108, %109, %110, %111}, %112, %113, p, 1, 1, 0, %115;\n}\n"
        : "+f"(d[0]), "+f"(d[1]), "+f"(d[2]), "+f"(d[3]), "+f"(d[4]), "+f"(d[5]), "+f"(d[6]), "+f"(d[7]), "+f"(d[8]), "+f"(d[9]), "+f"(d[10]), "+f"(d[11]), "+f"(d[12]), "+f"(d[13]), "+f"(d[14]), "+f"(d[15]), "+f"(d[16]), "+f"(d[17]), "+f"(d[18]), "+f"(d[19]), "+f"(d[20]), "+f"(d[21]), "+f"(d[22]), "+f"(d[23]), "+f"(d[24]), "+f"(d[25]), "+f"(d[26]), "+f"(d[27]), "+f"(d[28]), "+f"(d[29]), "+f"(d[30]), "+f"(d[31]), "+f"(d[32]), "+f"(d[33]), "+f"(d[34]), "+f"(d[35]), "+f"(d[36]), "+f"(d[37]), "+f"(d[38]), "+f"(d[39]), "+f"(d[40]), "+f"(d[41]), "+f"(d[42]), "+f"(d[43]), "+f"(d[44]), "+f"(d[45]), "+f"(d[46]), "+f"(d[47]), "+f"(d[48]), "+f"(d[49]), "+f"(d[50]), "+f"(d[51]), "+f"(d[52]), "+f"(d[53]), "+f"(d[54]), "+f"(d[55]), "+f"(d[56]), "+f"(d[57]), "+f"(d[58]), "+f"(d[59]), "+f"(d[60]), "+f"(d[61]), "+f"(d[62]), "+f"(d[63]), "+f"(d[64]), "+f"(d[65]), "+f"(d[66]), "+f"(d[67]), "+f"(d[68]), "+f"(d[69]), "+f"(d[70]), "+f"(d[71]), "+f"(d[72]), "+f"(d[73]), "+f"(d[74]), "+f"(d[75]), "+f"(d[76]), "+f"(d[77]), "+f"(d[78]), "+f"(d[79]), "+f"(d[80]), "+f"(d[81]), "+f"(d[82]), "+f"(d[83]), "+f"(d[84]), "+f"(d[85]), "+f"(d[86]), "+f"(d[87]), "+f"(d[88]), "+f"(d[89]), "+f"(d[90]), "+f"(d[91]), "+f"(d[92]), "+f"(d[93]), "+f"(d[94]), "+f"(d[95]), "+f"(d[96]), "+f"(d[97]), "+f"(d[98]), "+f"(d[99]), "+f"(d[100]), "+f"(d[101]), "+f"(d[102]), "+f"(d[103]), "+f"(d[104]), "+f"(d[105]), "+f"(d[106]), "+f"(d[107]), "+f"(d[108]), "+f"(d[109]), "+f"(d[110]), "+f"(d[111])
        : "l"(da), "l"(db), "r"(scaleD), "n"(TB));
}

constexpr int S1_STAGES = 7;
constexpr int S1_XN = 0;
constexpr int S1_B = 7 * 16384;
constexpr int Y_STAGES = 5, Y_STAGE = 45056;
constexpr int F_STAGES = 4, F_STAGE = 49152;
constexpr int BAR = S1_B + S1_STAGES * 16384;
constexpr int BAR_F1 = BAR, BAR_E1 = BAR + 56, BAR_F2 = BAR + 112, BAR_E2 = BAR + 152, BAR_S1DONE = BAR + 192;
constexpr int BAR_PUB = BAR + 208;
constexpr int DEP_CNT = BAR + 200;
constexpr int SMEM_BYTES = BAR + 256 + 1024;
constexpr int TPITCH = 464;

__device__ __forceinline__ int n_passes(int j) { return j < 4 ? 2 : (j < 6 ? 4 : (j == 6 ? 10 : 9)); }
__device__ __forceinline__ int pass_slab(int j, int p) {
    if (p == 0) return j < 7 ? -1 : 0;
    if (p == 1) return 1 + j;
    if (p < 4) return 4 * p - 3 + j;
    return 17 + 2 * (p - 4) + (j - 6);
}

template <int TB>
__device__ __forceinline__ void s1_mainloop(float (&acc)[2][64], uint32_t sb, int idx, int lane, int handoff) {
    int st = idx % S1_STAGES;
    uint32_t ph = (idx / S1_STAGES) & 1;
    int prev = 0;
    uint64_t da = mkdesc(sb + S1_XN, 16, 1024);
    const uint64_t db0 = TB ? mkdesc(sb + S1_B, 8192, 1024) : mkdesc(sb + S1_B, 16, 1024);
#pragma unroll 1
    for (int kb = 0; kb < 7; kb++) {
        mbar_wait(sb + BAR_F1 + 8 * st, ph);
        if (kb == 6 && handoff) asm volatile("bar.arrive %0, 256;" ::"r"(handoff) : "memory");
        const uint64_t db = db0 + st * 1024;
        wg_arrive();
#pragma unroll
        for (int s = 0; s < 4; s++) {
            wgmma_n128<TB>(acc[0], da + s * 2, db + s * (TB ? 128 : 2), kb | s);
            wgmma_n128<TB>(acc[1], da + 512 + s * 2, db + s * (TB ? 128 : 2), kb | s);
        }
        wg_commit();
        wg_wait<1>();
        if (kb > 0 && lane == 0) mbar_arrive_both(sb + BAR_E1 + 8 * prev);
        prev = st;
        da += 1024;
        if (++st == S1_STAGES) { st = 0; ph ^= 1; }
    }
    wg_wait<0>();
    if (lane == 0) mbar_arrive_both(sb + BAR_E1 + 8 * prev);
}

template <int TB>
__device__ __forceinline__ void s2_mainloop(float (&acc)[112], uint32_t sb, int wg, int lane) {
    constexpr int NST = TB ? F_STAGES : Y_STAGES, SSZ = TB ? F_STAGE : Y_STAGE, NKB = TB ? 28 : 32;
    int st = 0;
    uint32_t ph = 0;
    int prev = 0;
    const uint64_t da0 = mkdesc(sb + wg * 8192, 16, 1024);
    const uint64_t db0 = TB ? mkdesc(sb + 16384, 8192, 1024) : mkdesc(sb + 16384, 16, 1024);
#pragma unroll 1
    for (int i = 0; i < NKB; i++) {
        mbar_wait(sb + BAR_F2 + 8 * st, ph);
        const uint64_t da = da0 + st * (SSZ / 16), db = db0 + st * (SSZ / 16);
        wg_arrive();
#pragma unroll
        for (int s = 0; s < 4; s++) wgmma_n224<TB>(acc, da + s * 2, db + s * (TB ? 128 : 2), i | s);
        wg_commit();
        wg_wait<1>();
        if (i > 0 && lane == 0) mbar_arrive_both(sb + BAR_E2 + 8 * prev);
        prev = st;
        if (++st == NST) { st = 0; ph ^= 1; }
    }
    wg_wait<0>();
}

struct Maps {
    CUtensorMap wg, wu, hre, him, h, abT, sre, sim, wd;
};
struct Ptrs {
    const __nv_bfloat16 *x, *hre, *him, *wg, *wu, *wd;
    __nv_bfloat16* out;
};
__device__ __forceinline__ void mbar_arrive(uint32_t b) {
    asm volatile("mbarrier.arrive.shared::cta.b64 _, [%0];" ::"r"(b) : "memory");
}
__device__ __forceinline__ void l2_prefetch(const void* p, uint32_t bytes) {
    asm volatile("cp.async.bulk.prefetch.L2.global [%0], %1;" ::"l"(p), "r"(bytes) : "memory");
}
__device__ __forceinline__ void tma_prefetch(const CUtensorMap* m, int c0, int c1) {
    asm volatile("cp.async.bulk.prefetch.tensor.2d.L2.global.tile [%0, {%1, %2}];" ::"l"(m), "r"(c0), "r"(c1) : "memory");
}

__device__ __forceinline__ void dep_wait(uint32_t sb, uint32_t need) {
    uint32_t v;
    do { asm volatile("ld.acquire.cta.shared.u32 %0, [%1];" : "=r"(v) : "r"(sb + DEP_CNT) : "memory"); } while (v < need);
}

__global__ void __launch_bounds__(384, 1)
fused_kernel(const __grid_constant__ Ptrs pt, const __grid_constant__ Maps tm) {
    extern __shared__ unsigned char smem_raw[];
    const uint32_t sb = (s2u(smem_raw) + 1023) & ~1023u;
    const int tid = threadIdx.x, lane = tid & 31;
    const int warp = __shfl_sync(0xffffffffu, tid >> 5, 0);
    const int rank = blockIdx.x & 1;
    const int cid = blockIdx.x >> 1;
    const int j = cid & 7;
    const int rb = (cid >> 3) * 2 + rank;
    const int npass = n_passes(j);
    const int n = j & 1;
    const int part = j >> 1;

    {
        const int l8 = lane & 7, sub = lane >> 3;
        uint4 v[3][7];
#pragma unroll
        for (int it = 0; it < 3; it++) {
            const int qd = warp + 12 * it;
            if (qd < 32) {
                const uint4* src = reinterpret_cast<const uint4*>(pt.x + (size_t)(rb * 128 + qd * 4 + sub) * D_) + l8;
#pragma unroll
                for (int i = 0; i < 7; i++) v[it][i] = __ldg(src + i * 8);
            }
        }
        if (tid == 256) {
            TL(0, 0);
            for (int i = 0; i < S1_STAGES; i++) { mbar_init(sb + BAR_F1 + 8 * i, 1); mbar_init(sb + BAR_E1 + 8 * i, 8); }
            for (int i = 0; i < Y_STAGES; i++) { mbar_init(sb + BAR_F2 + 8 * i, 1); mbar_init(sb + BAR_E2 + 8 * i, 16); }
            mbar_init(sb + BAR_S1DONE, 16);
            mbar_init(sb + BAR_PUB, 4);
            mbar_init(sb + BAR_PUB + 8, 4);
            asm volatile("st.shared.u32 [%0], %1;" ::"r"(sb + DEP_CNT), "r"(0) : "memory");
            asm volatile("fence.mbarrier_init.release.cluster;" ::: "memory");
        }
        __syncwarp();
        asm volatile("barrier.cluster.arrive.relaxed.aligned;\nbarrier.cluster.wait.aligned;" ::: "memory");
        if (tid == 256) {
            const int slab = pass_slab(j, 0);
            for (int kb = 0; kb < 7; kb++) {
                const uint32_t dst = sb + S1_B + kb * 16384 + rank * 8192;
                const uint32_t fb = sb + BAR_F1 + 8 * kb;
                mbar_expect(fb, 16384);
                if (slab >= 0) {
                    tma_load_mc(dst, rank ? &tm.wu : &tm.wg, fb, slab * 64, kb * 64);
                } else {
                    const int a = 2 * j + rank;
                    tma_load_mc(dst, a < 7 ? &tm.hre : &tm.him, fb, kb * 64, (a < 7 ? a : a - 7) * 64);
                }
            }
            const int b = blockIdx.x;
            l2_prefetch((const char*)pt.wg + b * 12544, 12544);
            l2_prefetch((const char*)pt.wu + b * 12544, 12544);
            l2_prefetch((const char*)pt.wd + b * 12544, 12544);
        }
        __syncwarp();
        if (tid == 0) TL(0, 1);
#pragma unroll
        for (int it = 0; it < 3; it++) {
            const int qd = warp + 12 * it;
            if (qd < 32) {
                const int row = qd * 4 + sub;
                float s0 = 0.f, s1 = 0.f;
#pragma unroll
                for (int i = 0; i < 7; i++) {
                    s0 += (bf_lo(v[it][i].x) + bf_hi(v[it][i].x)) + (bf_lo(v[it][i].y) + bf_hi(v[it][i].y));
                    s1 += (bf_lo(v[it][i].z) + bf_hi(v[it][i].z)) + (bf_lo(v[it][i].w) + bf_hi(v[it][i].w));
                }
                float s = s0 + s1;
                s += __shfl_xor_sync(0xffffffffu, s, 1);
                s += __shfl_xor_sync(0xffffffffu, s, 2);
                s += __shfl_xor_sync(0xffffffffu, s, 4);
                if (it == 0 && tid == 0) TL(0, 3);
                const float mean = s * (1.0f / D_);
                float q0 = 0.f, q1 = 0.f;
#pragma unroll
                for (int i = 0; i < 7; i++) {
                    const uint32_t w[4] = {v[it][i].x, v[it][i].y, v[it][i].z, v[it][i].w};
#pragma unroll
                    for (int c = 0; c < 4; c++) {
                        const float d0 = bf_lo(w[c]) - mean, d1 = bf_hi(w[c]) - mean;
                        q0 = fmaf(d0, d0, q0);
                        q1 = fmaf(d1, d1, q1);
                    }
                }
                float q = q0 + q1;
                q += __shfl_xor_sync(0xffffffffu, q, 1);
                q += __shfl_xor_sync(0xffffffffu, q, 2);
                q += __shfl_xor_sync(0xffffffffu, q, 4);
                const float var = rbf(q * (1.0f / D_));
                const float den = rbf(sqrtf(rbf(var + 1e-5f)));
                const float rinv = 1.0f / den;
                const float rhi = rbf(rinv);
                const uint32_t m2 = pack_bf16(mean, mean), rhi2 = pack_bf16(rhi, rhi), rlo2 = pack_bf16(rinv - rhi, rinv - rhi);
                const uint32_t dst = sb + S1_XN + row * 128 + ((l8 ^ (row & 7)) << 4);
#pragma unroll
                for (int i = 0; i < 7; i++) {
                    const uint32_t w[4] = {v[it][i].x, v[it][i].y, v[it][i].z, v[it][i].w};
                    uint32_t o[4];
#pragma unroll
                    for (int c = 0; c < 4; c++) {
                        const uint32_t xc = hsub2(w[c], m2);
                        o[c] = hfma2(xc, rhi2, hmul2(xc, rlo2));
                    }
                    asm volatile("st.shared.v4.b32 [%0], {%1, %2, %3, %4};" ::"r"(dst + i * 16384), "r"(o[0]), "r"(o[1]), "r"(o[2]), "r"(o[3]) : "memory");
                }
            }
        }
        fence_async();
        __syncthreads();
        if (tid == 0) TL(0, 2);
    }

    if (warp >= 8) {
        asm volatile("setmaxnreg.dec.sync.aligned.u32 40;");
        if (warp == 8) {
            if (lane == 0) {
                int st = 0;
                uint32_t ph = 0;
                for (int p = 1; p < npass; p++) {
                    const int slab = pass_slab(j, p);
                    for (int kb = 0; kb < 7; kb++) {
                        mbar_wait(sb + BAR_E1 + 8 * st, ph);
                        const uint32_t fb = sb + BAR_F1 + 8 * st;
                        mbar_expect(fb, 16384);
                        tma_load_mc(sb + S1_B + st * 16384 + rank * 8192, rank ? &tm.wu : &tm.wg, fb, slab * 64, kb * 64);
                        if (++st == S1_STAGES) { st = 0; ph ^= 1; }
                    }
                }
                if (part < 3) {
                    mbar_wait(sb + BAR_S1DONE, 0);
                    TL(0, 24);
                    st = 0; ph = 1;
                    if (part < 2) {
                        const CUtensorMap* ma = part ? &tm.sim : &tm.sre;
                        for (int g = 0; g < 32; g++) {
                            mbar_wait(sb + BAR_E2 + 8 * st, ph);
                            const uint32_t dst = sb + st * Y_STAGE;
                            const uint32_t fb = sb + BAR_F2 + 8 * st;
                            mbar_expect(fb, Y_STAGE);
                            tma_load(dst, ma, fb, g * 64, rb * 128);
                            dep_wait(sb, (g >> 1) + 1);
                            tma_load_mc(dst + 16384 + rank * 14336, &tm.abT, fb, g * 64, part * 448 + n * 224 + rank * 112);
                            if (++st == Y_STAGES) { st = 0; ph ^= 1; }
                        }
                    } else {
                        for (int g = 0; g < 28; g++) {
                            mbar_wait(sb + BAR_E2 + 8 * st, ph);
                            const uint32_t dst = sb + st * F_STAGE;
                            const uint32_t fb = sb + BAR_F2 + 8 * st;
                            mbar_expect(fb, F_STAGE);
                            tma_load_mc(dst + 16384 + (2 * rank) * 8192, &tm.wd, fb, n * 224 + (2 * rank) * 64, g * 64);
                            tma_load_mc(dst + 16384 + (2 * rank + 1) * 8192, &tm.wd, fb, n * 224 + (2 * rank + 1) * 64, g * 64);
                            dep_wait(sb, g + 1);
                            tma_load(dst, &tm.h, fb, g * 64, rb * 128);
                            if (++st == F_STAGES) { st = 0; ph ^= 1; }
                        }
                    }
                }
            }
        } else if (warp == 9) {
            if (part < 3) {
                if (part < 2 && lane < 16) {
                    tma_prefetch(part ? &tm.sim : &tm.sre, (2 * lane + n) * 64, rb * 128);
                }
                const int ndep = part < 2 ? 16 : 29;
                const unsigned int epoch = *(volatile unsigned int*)&g_fl.done / gridDim.x + 1;
                const unsigned int* f = part < 2 ? &g_fl.ab[lane & 15] : (lane < 28 ? &g_fl.h[rb * 28 + lane] : &g_fl.y[rb * 2 + n]);
                const unsigned int target = (part < 2 ? 7 : (lane < 28 ? 1 : 16)) * epoch;
                bool ok = lane >= ndep;
                int published = 0;
                for (int spins = 0; published < ndep && spins < (1 << 22); spins++) {
                    if (!ok) {
                        unsigned int v;
                        asm volatile("ld.acquire.gpu.global.u32 %0, [%1];" : "=r"(v) : "l"(f) : "memory");
                        ok = (int)(v - target) >= 0;
                    }
                    const unsigned int m = __ballot_sync(0xffffffffu, ok);
                    const int cnt = min(__ffs(~m) - 1, ndep);
                    if (m == 0xffffffffu || cnt > published) {
                        published = (m == 0xffffffffu) ? ndep : cnt;
                        fence_async_all();
                        __syncwarp();
                        if (lane == 0) asm volatile("st.release.cta.shared.u32 [%0], %1;" ::"r"(sb + DEP_CNT), "r"(published) : "memory");
                    }
                }
                if (published < ndep && lane == 0)
                    asm volatile("st.release.cta.shared.u32 [%0], %1;" ::"r"(sb + DEP_CNT), "r"(ndep) : "memory");
            }
        } else {
            if (lane == 0) {
                const int w = warp - 10;
                uint32_t ph = 0;
                for (int p = w; p < npass; p += 2) {
                    const int slab = pass_slab(j, p);
                    mbar_wait(sb + BAR_PUB + 8 * w, ph);
                    ph ^= 1;
                    __threadfence();
                    flag_add(slab >= 0 ? &g_fl.h[rb * 28 + slab] : &g_fl.ab[rb]);
                }
            }
        }
        __syncwarp();
    } else {
        asm volatile("setmaxnreg.inc.sync.aligned.u32 232;");
        const int wg = warp >> 2, wl = warp & 3, wtid = tid & 127;
        const int qd = lane & 3;
        {
            float acc[2][64];
            for (int p = wg; p < npass; p += 2) {
                const int slab = pass_slab(j, p);
                if (p > 0) bar_sync(4 + (p & 1), 256);
                const int handoff = (p + 1 < npass) ? 4 + ((p + 1) & 1) : 0;
                if (slab >= 0) s1_mainloop<1>(acc, sb, p * 7, lane, handoff);
                else s1_mainloop<0>(acc, sb, p * 7, lane, handoff);
                if (p + 2 >= npass && lane == 0) mbar_arrive_both(sb + BAR_S1DONE);
                if (wtid == 0 && p < 4) TL(0, 4 + p);

                if (slab >= 0) {
                    __nv_bfloat16* dst = g_h + (size_t)(rb * 128 + wl * 16 + (lane >> 2)) * F_ + slab * 64 + qd * 8;
#pragma unroll
                    for (int mh = 0; mh < 2; mh++) {
#pragma unroll
                        for (int hh = 0; hh < 2; hh++) {
#pragma unroll
                            for (int g4 = 0; g4 < 2; g4++) {
                                uint32_t r[4];
#pragma unroll
                                for (int t = 0; t < 4; t++) {
                                    const int o = (g4 * 4 + t) * 4 + hh * 2;
                                    const uint32_t g2 = pack_bf16(acc[mh][o], acc[mh][o + 1]);
                                    const uint32_t u2 = pack_bf16(acc[mh][32 + o], acc[mh][32 + o + 1]);
                                    const uint32_t a2 = pack_bf16(gelu_tanh(bf_lo(g2)), gelu_tanh(bf_hi(g2)));
                                    r[t] = hmul2(a2, u2);
                                }
                                quad_transpose(r, qd);
                                __stcg(reinterpret_cast<uint4*>(dst + (size_t)(mh * 64 + hh * 8) * F_ + g4 * 32), make_uint4(r[0], r[1], r[2], r[3]));
                            }
                        }
                    }
                } else {
                    __nv_bfloat16* dst = g_abT + (size_t)(j * 128 + (qd >> 1) * 8 + (lane >> 2)) * ABP + rb * 128 + wl * 16 + (qd & 1) * 8;
#pragma unroll
                    for (int mh = 0; mh < 2; mh++) {
#pragma unroll
                        for (int jj = 0; jj < 16; jj += 2) {
                            uint32_t r[4];
#pragma unroll
                            for (int t = 0; t < 4; t++) {
                                const int o = (jj + (t >> 1)) * 4 + (t & 1) * 2;
                                r[t] = movmat_t(pack_bf16(acc[mh][o], acc[mh][o + 1]));
                            }
                            quad_transpose(r, qd);
                            __stcg(reinterpret_cast<uint4*>(dst + (size_t)(jj * 8) * ABP + mh * 64), make_uint4(r[0], r[1], r[2], r[3]));
                        }
                    }
                }
                __syncwarp();
                if (lane == 0) mbar_arrive(sb + BAR_PUB + 8 * wg);
                if (wtid == 0 && p < 4) TL(0, 10 + p);
            }
        }
        if (wtid == 0) TL(0, 20 + wg);
        if (part < 3) {
            {
                float acc[112];
                const size_t base = (size_t)(rb * 128 + wg * 64 + wl * 16 + (lane >> 2)) * D_ + n * 224 + qd * 8;
                if (part < 2) {
                    s2_mainloop<0>(acc, sb, wg, lane);
                    if (tid == 0) TL(0, 25);
                    uint4* dst = g_y + (size_t)((part * 32 + rb * 2 + n) * 14) * 256 + tid;
#pragma unroll
                    for (int i = 0; i < 14; i++)
                        __stcg(dst + i * 256, make_uint4(pack_bf16(acc[8 * i], acc[8 * i + 1]), pack_bf16(acc[8 * i + 2], acc[8 * i + 3]),
                                                         pack_bf16(acc[8 * i + 4], acc[8 * i + 5]), pack_bf16(acc[8 * i + 6], acc[8 * i + 7])));
                    __threadfence();
                    __syncwarp();
                    if (lane == 0) flag_add(&g_fl.y[rb * 2 + n]);
                } else {
                    uint4 xv[14];
#pragma unroll
                    for (int i = 0; i < 14; i++)
                        xv[i] = __ldg(reinterpret_cast<const uint4*>(pt.x + base + (i / 7) * 8 * D_ + (i % 7) * 32));
                    s2_mainloop<1>(acc, sb, wg, lane);
                    if (tid == 0) TL(0, 25);
                    dep_wait(sb, 29);
                    if (tid == 0) TL(0, 26);
                    const uint4* ysrc = g_y + (size_t)((rb * 2 + n) * 14) * 256 + tid;
                    uint4 yr[14], yi[14];
#pragma unroll
                    for (int i = 0; i < 14; i++) yr[i] = __ldcg(ysrc + i * 256);
                    uint32_t sg[56];
#pragma unroll
                    for (int i = 0; i < 56; i++) {
                        const uint32_t f2 = pack_bf16(acc[2 * i], acc[2 * i + 1]);
                        sg[i] = pack_bf16(silu(bf_lo(f2)), silu(bf_hi(f2)));
                    }
#pragma unroll
                    for (int i = 0; i < 14; i++) yi[i] = __ldcg(ysrc + (32 * 14 + i) * 256);
#pragma unroll
                    for (int i = 0; i < 14; i++) {
                        sg[4 * i + 0] = hmul2(hsub2(yr[i].x, yi[i].x), sg[4 * i + 0]);
                        sg[4 * i + 1] = hmul2(hsub2(yr[i].y, yi[i].y), sg[4 * i + 1]);
                        sg[4 * i + 2] = hmul2(hsub2(yr[i].z, yi[i].z), sg[4 * i + 2]);
                        sg[4 * i + 3] = hmul2(hsub2(yr[i].w, yi[i].w), sg[4 * i + 3]);
                    }
#pragma unroll
                    for (int hh = 0; hh < 2; hh++) {
#pragma unroll
                        for (int g4 = 0; g4 < 7; g4++) {
                            uint32_t r[4];
#pragma unroll
                            for (int t = 0; t < 4; t++) r[t] = sg[(g4 * 4 + t) * 2 + hh];
                            quad_transpose(r, qd);
                            const uint4 xx = xv[hh * 7 + g4];
                            *reinterpret_cast<uint4*>(pt.out + base + hh * 8 * D_ + g4 * 32) =
                                make_uint4(hadd2(xx.x, r[0]), hadd2(xx.y, r[1]), hadd2(xx.z, r[2]), hadd2(xx.w, r[3]));
                        }
                    }
                }
            }
        }
    }
    if (tid == 0) TL(0, 29);
    cluster_sync();
    if (tid == 0) {
        TL(0, 30);
        atomicAdd(&g_fl.done, 1u);
    }
}

typedef CUresult (*EncFn)(CUtensorMap*, CUtensorMapDataType, cuuint32_t, void*, const cuuint64_t*, const cuuint64_t*,
                          const cuuint32_t*, const cuuint32_t*, CUtensorMapInterleave, CUtensorMapSwizzle,
                          CUtensorMapL2promotion, CUtensorMapFloatOOBfill);

void make_map(EncFn enc, CUtensorMap* m, const void* ptr, int rows, int cols, int box_rows, int box_cols, int pitch = 0) {
    const bool swz = true;
    cuuint64_t gd[2] = {(cuuint64_t)cols, (cuuint64_t)rows};
    cuuint64_t gs[1] = {(cuuint64_t)(pitch ? pitch : cols) * 2};
    cuuint32_t bx[2] = {(cuuint32_t)box_cols, (cuuint32_t)box_rows};
    cuuint32_t es[2] = {1, 1};
    enc(m, CU_TENSOR_MAP_DATA_TYPE_BFLOAT16, 2, const_cast<void*>(ptr), gd, gs, bx, es, CU_TENSOR_MAP_INTERLEAVE_NONE,
        swz ? CU_TENSOR_MAP_SWIZZLE_128B : CU_TENSOR_MAP_SWIZZLE_NONE, CU_TENSOR_MAP_L2_PROMOTION_L2_128B,
        CU_TENSOR_MAP_FLOAT_OOB_FILL_NONE);
}

}

extern "C" void kernel_launch(void* const* d_in, const int* in_sizes, int n_in, void* d_out, int out_size) {
    Ptrs pt;
    pt.x = (const __nv_bfloat16*)d_in[0];
    pt.hre = (const __nv_bfloat16*)d_in[3];
    pt.him = (const __nv_bfloat16*)d_in[4];
    pt.wg = (const __nv_bfloat16*)d_in[6];
    pt.wu = (const __nv_bfloat16*)d_in[7];
    pt.wd = (const __nv_bfloat16*)d_in[8];
    pt.out = (__nv_bfloat16*)d_out;

    void* fn = nullptr;
    cudaDriverEntryPointQueryResult qr;
    cudaGetDriverEntryPoint("cuTensorMapEncodeTiled", &fn, cudaEnableDefault, &qr);
    EncFn enc = (EncFn)fn;
    void *p_abT, *p_h;
    cudaGetSymbolAddress(&p_abT, g_abT);
    cudaGetSymbolAddress(&p_h, g_h);

    Maps tm;
    make_map(enc, &tm.wg, d_in[6], D_, F_, 64, 64);
    make_map(enc, &tm.wu, d_in[7], D_, F_, 64, 64);
    make_map(enc, &tm.hre, d_in[3], D_, D_, 64, 64);
    make_map(enc, &tm.him, d_in[4], D_, D_, 64, 64);
    make_map(enc, &tm.h, p_h, S_, F_, 128, 64);
    make_map(enc, &tm.abT, p_abT, 896, S_, 112, 64, ABP);
    make_map(enc, &tm.sre, d_in[1], S_, S_, 128, 64);
    make_map(enc, &tm.sim, d_in[2], S_, S_, 128, 64);
    make_map(enc, &tm.wd, d_in[8], F_, D_, 64, 64);

    cudaFuncSetAttribute(fused_kernel, cudaFuncAttributeMaxDynamicSharedMemorySize, SMEM_BYTES);

    cudaLaunchAttribute at[1];
    at[0].id = cudaLaunchAttributeClusterDimension;
    at[0].val.clusterDim.x = 2; at[0].val.clusterDim.y = 1; at[0].val.clusterDim.z = 1;
    cudaLaunchConfig_t cfg = {};
    cfg.gridDim = dim3(128); cfg.blockDim = dim3(384); cfg.stream = cudaStreamPerThread;
    cfg.attrs = at; cfg.numAttrs = 1;
    cfg.dynamicSmemBytes = SMEM_BYTES;
    cudaLaunchKernelEx(&cfg, fused_kernel, pt, tm);
}
```

```cpp
#include <cuda_runtime.h>
#include <cuda_bf16.h>
#include <cuda.h>
#include <stdint.h>

namespace {

constexpr int S_ = 2048, D_ = 448, F_ = 1792;

constexpr int ABP = 2048 + 64;
__device__ __align__(1024) __nv_bfloat16 g_abT[896 * ABP];
__device__ __align__(1024) __nv_bfloat16 g_h[2048 * 1792];
__device__ __align__(1024) uint4 g_y[2 * 32 * 14 * 256];
struct Flags {
    unsigned int ab[16];
    unsigned int h[16 * 28];
    unsigned int y[32];
    unsigned int done;
};
__device__ Flags g_fl;

#define TL(k, i) do {} while (0)
__device__ __forceinline__ uint32_t s2u(const void* p) { return (uint32_t)__cvta_generic_to_shared(p); }
__device__ __forceinline__ void mbar_init(uint32_t b, int c) {
    asm volatile("mbarrier.init.shared::cta.b64 [%0], %1;" ::"r"(b), "r"(c));
}
__device__ __forceinline__ void mbar_expect(uint32_t b, uint32_t bytes) {
    asm volatile("mbarrier.arrive.expect_tx.shared::cta.b64 _, [%0], %1;" ::"r"(b), "r"(bytes) : "memory");
}
__device__ __forceinline__ void mbar_wait(uint32_t b, uint32_t ph) {
    uint32_t ok;
    do {
        asm volatile("{\n.reg .pred p;\nmbarrier.try_wait.parity.shared::cta.b64 p, [%1], %2;\nselp.u32 %0, 1, 0, p;\n}"
                     : "=r"(ok) : "r"(b), "r"(ph) : "memory");
    } while (!ok);
}
__device__ __forceinline__ void mbar_arrive_both(uint32_t b) {
    asm volatile("{\n.reg .b32 r0, r1;\n"
                 "mapa.shared::cluster.u32 r0, %0, 0;\n"
                 "mapa.shared::cluster.u32 r1, %0, 1;\n"
                 "mbarrier.arrive.shared::cluster.b64 _, [r0];\n"
                 "mbarrier.arrive.shared::cluster.b64 _, [r1];\n}"
                 ::"r"(b) : "memory");
}
__device__ __forceinline__ void tma_load(uint32_t dst, const CUtensorMap* m, uint32_t bar, int c0, int c1) {
    asm volatile("cp.async.bulk.tensor.2d.shared::cluster.global.mbarrier::complete_tx::bytes [%0], [%1, {%3, %4}], [%2];"
                 ::"r"(dst), "l"(m), "r"(bar), "r"(c0), "r"(c1) : "memory");
}
__device__ __forceinline__ void tma_load_mc(uint32_t dst, const CUtensorMap* m, uint32_t bar, int c0, int c1) {
    asm volatile("cp.async.bulk.tensor.2d.shared::cluster.global.mbarrier::complete_tx::bytes.multicast::cluster [%0], [%1, {%3, %4}], [%2], %5;"
                 ::"r"(dst), "l"(m), "r"(bar), "r"(c0), "r"(c1), "h"((uint16_t)3) : "memory");
}
__device__ __forceinline__ void tma_store(const CUtensorMap* m, uint32_t src, int c0, int c1) {
    asm volatile("cp.async.bulk.tensor.2d.global.shared::cta.bulk_group [%0, {%2, %3}], [%1];"
                 ::"l"(m), "r"(src), "r"(c0), "r"(c1) : "memory");
}
__device__ __forceinline__ void bulk_commit() { asm volatile("cp.async.bulk.commit_group;" ::: "memory"); }
__device__ __forceinline__ void bulk_wait_read0() { asm volatile("cp.async.bulk.wait_group.read 0;" ::: "memory"); }
__device__ __forceinline__ void bulk_wait0() { asm volatile("cp.async.bulk.wait_group 0;" ::: "memory"); }
__device__ __forceinline__ void fence_async() { asm volatile("fence.proxy.async.shared::cta;" ::: "memory"); }
__device__ __forceinline__ void fence_async_all() { asm volatile("fence.proxy.async;" ::: "memory"); }
__device__ __forceinline__ void cluster_sync() {
    asm volatile("barrier.cluster.arrive.release.aligned;\nbarrier.cluster.wait.acquire.aligned;" ::: "memory");
}
__device__ __forceinline__ void bar_sync(int id, int n) { asm volatile("bar.sync %0, %1;" ::"r"(id), "r"(n) : "memory"); }
__device__ __forceinline__ void wg_arrive() { asm volatile("wgmma.fence.sync.aligned;" ::: "memory"); }
__device__ __forceinline__ void wg_commit() { asm volatile("wgmma.commit_group.sync.aligned;" ::: "memory"); }
template <int N> __device__ __forceinline__ void wg_wait() { asm volatile("wgmma.wait_group.sync.aligned %0;" ::"n"(N) : "memory"); }
__device__ __forceinline__ void stmat4(uint32_t a, uint32_t r0, uint32_t r1, uint32_t r2, uint32_t r3) {
    asm volatile("stmatrix.sync.aligned.m8n8.x4.shared.b16 [%0], {%1, %2, %3, %4};" ::"r"(a), "r"(r0), "r"(r1), "r"(r2), "r"(r3) : "memory");
}
__device__ __forceinline__ void stmat4t(uint32_t a, uint32_t r0, uint32_t r1, uint32_t r2, uint32_t r3) {
    asm volatile("stmatrix.sync.aligned.m8n8.x4.trans.shared.b16 [%0], {%1, %2, %3, %4};" ::"r"(a), "r"(r0), "r"(r1), "r"(r2), "r"(r3) : "memory");
}
__device__ __forceinline__ void ldmat4(uint32_t a, uint32_t (&r)[4]) {
    asm volatile("ldmatrix.sync.aligned.m8n8.x4.shared.b16 {%0, %1, %2, %3}, [%4];"
                 : "=r"(r[0]), "=r"(r[1]), "=r"(r[2]), "=r"(r[3]) : "r"(a) : "memory");
}
__device__ __forceinline__ void flag_add(unsigned int* f) {
    asm volatile("red.release.gpu.global.add.u32 [%0], 1;" ::"l"(f) : "memory");
}
__device__ __forceinline__ void flag_wait(const unsigned int* f, unsigned int target) {
    unsigned int v;
    int spins = 0;
    while (true) {
        asm volatile("ld.acquire.gpu.global.u32 %0, [%1];" : "=r"(v) : "l"(f) : "memory");
        if ((int)(v - target) >= 0 || ++spins > (1 << 22)) break;
    }
}
__device__ __forceinline__ void quad_transpose(uint32_t (&r)[4], int q) {
    const bool o1 = q & 1, o2 = q & 2;
    uint32_t a = o1 ? r[0] : r[1], b = o1 ? r[2] : r[3];
    a = __shfl_xor_sync(0xffffffffu, a, 1);
    b = __shfl_xor_sync(0xffffffffu, b, 1);
    if (o1) { r[0] = a; r[2] = b; } else { r[1] = a; r[3] = b; }
    a = o2 ? r[0] : r[2]; b = o2 ? r[1] : r[3];
    a = __shfl_xor_sync(0xffffffffu, a, 2);
    b = __shfl_xor_sync(0xffffffffu, b, 2);
    if (o2) { r[0] = a; r[1] = b; } else { r[2] = a; r[3] = b; }
}
__device__ __forceinline__ uint32_t movmat_t(uint32_t v) {
    uint32_t r;
    asm volatile("movmatrix.sync.aligned.m8n8.trans.b16 %0, %1;" : "=r"(r) : "r"(v));
    return r;
}
__device__ __forceinline__ uint64_t mkdesc(uint32_t addr, uint32_t lbo, uint32_t sbo) {
    return (uint64_t)((addr & 0x3FFFF) >> 4) | ((uint64_t)(lbo >> 4) << 16) | ((uint64_t)(sbo >> 4) << 32) | (1ull << 62);
}
__device__ __forceinline__ uint32_t pack_bf16(float lo, float hi) {
    uint32_t r;
    asm("cvt.rn.bf16x2.f32 %0, %1, %2;" : "=r"(r) : "f"(hi), "f"(lo));
    return r;
}
__device__ __forceinline__ uint32_t hsub2(uint32_t a, uint32_t b) { uint32_t r; asm("sub.rn.bf16x2 %0, %1, %2;" : "=r"(r) : "r"(a), "r"(b)); return r; }
__device__ __forceinline__ uint32_t hadd2(uint32_t a, uint32_t b) { uint32_t r; asm("add.rn.bf16x2 %0, %1, %2;" : "=r"(r) : "r"(a), "r"(b)); return r; }
__device__ __forceinline__ uint32_t hmul2(uint32_t a, uint32_t b) { uint32_t r; asm("mul.rn.bf16x2 %0, %1, %2;" : "=r"(r) : "r"(a), "r"(b)); return r; }
__device__ __forceinline__ uint32_t hfma2(uint32_t a, uint32_t b, uint32_t c) { uint32_t r; asm("fma.rn.bf16x2 %0, %1, %2, %3;" : "=r"(r) : "r"(a), "r"(b), "r"(c)); return r; }
__device__ __forceinline__ float bf_lo(uint32_t u) { return __uint_as_float(u << 16); }
__device__ __forceinline__ float bf_hi(uint32_t u) { return __uint_as_float(u & 0xffff0000u); }
__device__ __forceinline__ float rbf(float v) { return __bfloat162float(__float2bfloat16_rn(v)); }
__device__ __forceinline__ float tanh_fast(float x) { float r; asm("tanh.approx.f32 %0, %1;" : "=f"(r) : "f"(x)); return r; }
__device__ __forceinline__ float gelu_tanh(float x) {
    float u = x * fmaf(x * x, 0.0356774081f, 0.7978845608f);
    float hx = 0.5f * x;
    return fmaf(hx, tanh_fast(u), hx);
}
__device__ __forceinline__ float silu(float f) { const float hf = 0.5f * f; return fmaf(hf, tanh_fast(hf), hf); }

template <int TB>
__device__ __forceinline__ void wgmma_n128(float (&d)[64], uint64_t da, uint64_t db, int scaleD) {
    asm volatile("{\n.reg .pred p;\nsetp.ne.b32 p, %66, 0;\n"
        "wgmma.mma_async.sync.aligned.m64n128k16.f32.bf16.bf16 {%0, %1, %2, %3, %4, %5, %6, %7, %8, %9, %10, %11, %12, %13, %14, %15, %16, %17, %18, %19, %20, %21, %22, %23, %24, %25, %26, %27, %28, %29, %30, %31, %32, %33, %34, %35, %36, %37, %38, %39, %40, %41, %42, %43, %44, %45, %46, %47, %48, %49, %50, %51, %52, %53, %54, %55, %56, %57, %58, %59, %60, %61, %62, %63}, %64, %65, p, 1, 1, 0, %67;\n}\n"
        : "+f"(d[0]), "+f"(d[1]), "+f"(d[2]), "+f"(d[3]), "+f"(d[4]), "+f"(d[5]), "+f"(d[6]), "+f"(d[7]), "+f"(d[8]), "+f"(d[9]), "+f"(d[10]), "+f"(d[11]), "+f"(d[12]), "+f"(d[13]), "+f"(d[14]), "+f"(d[15]), "+f"(d[16]), "+f"(d[17]), "+f"(d[18]), "+f"(d[19]), "+f"(d[20]), "+f"(d[21]), "+f"(d[22]), "+f"(d[23]), "+f"(d[24]), "+f"(d[25]), "+f"(d[26]), "+f"(d[27]), "+f"(d[28]), "+f"(d[29]), "+f"(d[30]), "+f"(d[31]), "+f"(d[32]), "+f"(d[33]), "+f"(d[34]), "+f"(d[35]), "+f"(d[36]), "+f"(d[37]), "+f"(d[38]), "+f"(d[39]), "+f"(d[40]), "+f"(d[41]), "+f"(d[42]), "+f"(d[43]), "+f"(d[44]), "+f"(d[45]), "+f"(d[46]), "+f"(d[47]), "+f"(d[48]), "+f"(d[49]), "+f"(d[50]), "+f"(d[51]), "+f"(d[52]), "+f"(d[53]), "+f"(d[54]), "+f"(d[55]), "+f"(d[56]), "+f"(d[57]), "+f"(d[58]), "+f"(d[59]), "+f"(d[60]), "+f"(d[61]), "+f"(d[62]), "+f"(d[63])
        : "l"(da), "l"(db), "r"(scaleD), "n"(TB));
}
template <int TB>
__device__ __forceinline__ void wgmma_n224(float (&d)[112], uint64_t da, uint64_t db, int scaleD) {
    asm volatile("{\n.reg .pred p;\nsetp.ne.b32 p, %114, 0;\n"
        "wgmma.mma_async.sync.aligned.m64n224k16.f32.bf16.bf16 {%0, %1, %2, %3, %4, %5, %6, %7, %8, %9, %10, %11, %12, %13, %14, %15, %16, %17, %18, %19, %20, %21, %22, %23, %24, %25, %26, %27, %28, %29, %30, %31, %32, %33, %34, %35, %36, %37, %38, %39, %40, %41, %42, %43, %44, %45, %46, %47, %48, %49, %50, %51, %52, %53, %54, %55, %56, %57, %58, %59, %60, %61, %62, %63, %64, %65, %66, %67, %68, %69, %70, %71, %72, %73, %74, %75, %76, %77, %78, %79, %80, %81, %82, %83, %84, %85, %86, %87, %88, %89, %90, %91, %92, %93, %94, %95, %96, %97, %98, %99, %100, %101, %102, %103, %104, %105, %106, %107, %108, %109, %110, %111}, %112, %113, p, 1, 1, 0, %115;\n}\n"
        : "+f"(d[0]), "+f"(d[1]), "+f"(d[2]), "+f"(d[3]), "+f"(d[4]), "+f"(d[5]), "+f"(d[6]), "+f"(d[7]), "+f"(d[8]), "+f"(d[9]), "+f"(d[10]), "+f"(d[11]), "+f"(d[12]), "+f"(d[13]), "+f"(d[14]), "+f"(d[15]), "+f"(d[16]), "+f"(d[17]), "+f"(d[18]), "+f"(d[19]), "+f"(d[20]), "+f"(d[21]), "+f"(d[22]), "+f"(d[23]), "+f"(d[24]), "+f"(d[25]), "+f"(d[26]), "+f"(d[27]), "+f"(d[28]), "+f"(d[29]), "+f"(d[30]), "+f"(d[31]), "+f"(d[32]), "+f"(d[33]), "+f"(d[34]), "+f"(d[35]), "+f"(d[36]), "+f"(d[37]), "+f"(d[38]), "+f"(d[39]), "+f"(d[40]), "+f"(d[41]), "+f"(d[42]), "+f"(d[43]), "+f"(d[44]), "+f"(d[45]), "+f"(d[46]), "+f"(d[47]), "+f"(d[48]), "+f"(d[49]), "+f"(d[50]), "+f"(d[51]), "+f"(d[52]), "+f"(d[53]), "+f"(d[54]), "+f"(d[55]), "+f"(d[56]), "+f"(d[57]), "+f"(d[58]), "+f"(d[59]), "+f"(d[60]), "+f"(d[61]), "+f"(d[62]), "+f"(d[63]), "+f"(d[64]), "+f"(d[65]), "+f"(d[66]), "+f"(d[67]), "+f"(d[68]), "+f"(d[69]), "+f"(d[70]), "+f"(d[71]), "+f"(d[72]), "+f"(d[73]), "+f"(d[74]), "+f"(d[75]), "+f"(d[76]), "+f"(d[77]), "+f"(d[78]), "+f"(d[79]), "+f"(d[80]), "+f"(d[81]), "+f"(d[82]), "+f"(d[83]), "+f"(d[84]), "+f"(d[85]), "+f"(d[86]), "+f"(d[87]), "+f"(d[88]), "+f"(d[89]), "+f"(d[90]), "+f"(d[91]), "+f"(d[92]), "+f"(d[93]), "+f"(d[94]), "+f"(d[95]), "+f"(d[96]), "+f"(d[97]), "+f"(d[98]), "+f"(d[99]), "+f"(d[100]), "+f"(d[101]), "+f"(d[102]), "+f"(d[103]), "+f"(d[104]), "+f"(d[105]), "+f"(d[106]), "+f"(d[107]), "+f"(d[108]), "+f"(d[109]), "+f"(d[110]), "+f"(d[111])
        : "l"(da), "l"(db), "r"(scaleD), "n"(TB));
}

constexpr int S1_STAGES = 7;
constexpr int S1_XN = 0;
constexpr int S1_B = 7 * 16384;
constexpr int Y_STAGES = 5, Y_STAGE = 45056;
constexpr int F_STAGES = 4, F_STAGE = 49152;
constexpr int BAR = S1_B + S1_STAGES * 16384;
constexpr int BAR_F1 = BAR, BAR_E1 = BAR + 56, BAR_F2 = BAR + 112, BAR_E2 = BAR + 152, BAR_S1DONE = BAR + 192;
constexpr int BAR_PUB = BAR + 208;
constexpr int DEP_CNT = BAR + 200;
constexpr int SMEM_BYTES = BAR + 256 + 1024;
constexpr int TPITCH = 464;

__device__ __forceinline__ int n_passes(int j) { return j < 4 ? 2 : (j < 6 ? 4 : (j == 6 ? 10 : 9)); }
__device__ __forceinline__ int pass_slab(int j, int p) {
    if (p == 0) return j < 7 ? -1 : 0;
    if (p == 1) return 1 + j;
    if (p < 4) return 4 * p - 3 + j;
    return 17 + 2 * (p - 4) + (j - 6);
}

template <int TB>
__device__ __forceinline__ void s1_mainloop(float (&acc)[2][64], uint32_t sb, int p, int lane, int handoff) {
    const uint32_t ph = p & 1;
    uint64_t dx = mkdesc(sb + S1_XN, 16, 1024);
    uint64_t dw = TB ? mkdesc(sb + S1_B, 8192, 1024) : mkdesc(sb + S1_B, 16, 1024);
    const bool rel = handoff != 0 && lane == 0;
#pragma unroll 1
    for (int kb = 0; kb < 7; kb++) {
        mbar_wait(sb + BAR_F1 + 8 * kb, ph);
        if (kb == 6 && handoff) asm volatile("bar.arrive %0, 256;" ::"r"(handoff) : "memory");
        wg_arrive();
#pragma unroll
        for (int s = 0; s < 4; s++) {
            if (TB) {
                wgmma_n128<1>(acc[0], dx + s * 2, dw + s * 128, kb | s);
                wgmma_n128<1>(acc[1], dx + 512 + s * 2, dw + s * 128, kb | s);
            } else {
                wgmma_n128<0>(acc[0], dw + s * 2, dx + s * 2, kb | s);
                wgmma_n128<0>(acc[1], dw + 512 + s * 2, dx + s * 2, kb | s);
            }
        }
        wg_commit();
        wg_wait<1>();
        if (kb > 0 && rel) mbar_arrive_both(sb + BAR_E1 + 8 * (kb - 1));
        dx += 1024;
        dw += 1024;
    }
    wg_wait<0>();
    if (rel) mbar_arrive_both(sb + BAR_E1 + 8 * 6);
}

template <int TB>
__device__ __forceinline__ void s2_mainloop(float (&acc)[112], uint32_t sb, int wg, int lane) {
    constexpr int NST = TB ? F_STAGES : Y_STAGES, SSZ = TB ? F_STAGE : Y_STAGE, NKB = TB ? 28 : 32;
    int st = 0;
    uint32_t ph = 0;
    int prev = 0;
    const uint64_t da0 = mkdesc(sb + wg * 8192, 16, 1024);
    const uint64_t db0 = TB ? mkdesc(sb + 16384, 8192, 1024) : mkdesc(sb + 16384, 16, 1024);
#pragma unroll 1
    for (int i = 0; i < NKB; i++) {
        mbar_wait(sb + BAR_F2 + 8 * st, ph);
        const uint64_t da = da0 + st * (SSZ / 16), db = db0 + st * (SSZ / 16);
        wg_arrive();
#pragma unroll
        for (int s = 0; s < 4; s++) wgmma_n224<TB>(acc, da + s * 2, db + s * (TB ? 128 : 2), i | s);
        wg_commit();
        wg_wait<1>();
        if (i > 0 && i <= NKB - NST && lane == 0) mbar_arrive_both(sb + BAR_E2 + 8 * prev);
        prev = st;
        if (++st == NST) { st = 0; ph ^= 1; }
    }
    wg_wait<0>();
}

struct Maps {
    CUtensorMap wg, wu, hre, him, h, abT, sre, sim, wd;
};
struct Ptrs {
    const __nv_bfloat16 *x, *hre, *him, *wg, *wu, *wd;
    __nv_bfloat16* out;
};
__device__ __forceinline__ void mbar_arrive(uint32_t b) {
    asm volatile("mbarrier.arrive.shared::cta.b64 _, [%0];" ::"r"(b) : "memory");
}
__device__ __forceinline__ void l2_prefetch(const void* p, uint32_t bytes) {
    asm volatile("cp.async.bulk.prefetch.L2.global [%0], %1;" ::"l"(p), "r"(bytes) : "memory");
}
__device__ __forceinline__ void tma_prefetch(const CUtensorMap* m, int c0, int c1) {
    asm volatile("cp.async.bulk.prefetch.tensor.2d.L2.global.tile [%0, {%1, %2}];" ::"l"(m), "r"(c0), "r"(c1) : "memory");
}

__device__ __forceinline__ void dep_wait(uint32_t sb, uint32_t need) {
    uint32_t v;
    do { asm volatile("ld.acquire.cta.shared.u32 %0, [%1];" : "=r"(v) : "r"(sb + DEP_CNT) : "memory"); } while (v < need);
}

__global__ void __launch_bounds__(384, 1)
fused_kernel(const __grid_constant__ Ptrs pt, const __grid_constant__ Maps tm) {
    extern __shared__ unsigned char smem_raw[];
    const uint32_t sb = (s2u(smem_raw) + 1023) & ~1023u;
    const int tid = threadIdx.x, lane = tid & 31;
    const int warp = __shfl_sync(0xffffffffu, tid >> 5, 0);
    const int rank = blockIdx.x & 1;
    const int cid = blockIdx.x >> 1;
    const int j = cid & 7;
    const int rb = (cid >> 3) * 2 + rank;
    const int npass = n_passes(j);
    const int n = j & 1;
    const int part = j >> 1;

    {
        const int l8 = lane & 7, sub = lane >> 3;
        uint4 v[3][7];
#pragma unroll
        for (int it = 0; it < 3; it++) {
            const int qd = warp + 12 * it;
            if (qd < 32) {
                const uint4* src = reinterpret_cast<const uint4*>(pt.x + (size_t)(rb * 128 + qd * 4 + sub) * D_) + l8;
#pragma unroll
                for (int i = 0; i < 7; i++) v[it][i] = __ldg(src + i * 8);
            }
        }
        if (tid == 256) {
            TL(0, 0);
            for (int i = 0; i < S1_STAGES; i++) { mbar_init(sb + BAR_F1 + 8 * i, 1); mbar_init(sb + BAR_E1 + 8 * i, 8); }
            for (int i = 0; i < Y_STAGES; i++) { mbar_init(sb + BAR_F2 + 8 * i, 1); mbar_init(sb + BAR_E2 + 8 * i, 16); }
            mbar_init(sb + BAR_S1DONE, 16);
            mbar_init(sb + BAR_PUB, 4);
            mbar_init(sb + BAR_PUB + 8, 4);
            asm volatile("st.shared.u32 [%0], %1;" ::"r"(sb + DEP_CNT), "r"(0) : "memory");
            asm volatile("fence.mbarrier_init.release.cluster;" ::: "memory");
        }
        __syncwarp();
        asm volatile("barrier.cluster.arrive.relaxed.aligned;\nbarrier.cluster.wait.aligned;" ::: "memory");
        if (tid == 256) {
            const int slab = pass_slab(j, 0);
            for (int kb = 0; kb < 7; kb++) {
                const uint32_t dst = sb + S1_B + kb * 16384 + rank * 8192;
                const uint32_t fb = sb + BAR_F1 + 8 * kb;
                mbar_expect(fb, 16384);
                if (slab >= 0) {
                    tma_load_mc(dst, rank ? &tm.wu : &tm.wg, fb, slab * 64, kb * 64);
                } else {
                    const int a = 2 * j + rank;
                    tma_load_mc(dst, a < 7 ? &tm.hre : &tm.him, fb, kb * 64, (a < 7 ? a : a - 7) * 64);
                }
            }
            const int b = blockIdx.x;
            l2_prefetch((const char*)pt.wg + b * 12544, 12544);
            l2_prefetch((const char*)pt.wu + b * 12544, 12544);
            l2_prefetch((const char*)pt.wd + b * 12544, 12544);
        }
        __syncwarp();
        if (tid == 0) TL(0, 1);
#pragma unroll
        for (int it = 0; it < 3; it++) {
            const int qd = warp + 12 * it;
            if (qd < 32) {
                const int row = qd * 4 + sub;
                float s0 = 0.f, s1 = 0.f;
#pragma unroll
                for (int i = 0; i < 7; i++) {
                    s0 += (bf_lo(v[it][i].x) + bf_hi(v[it][i].x)) + (bf_lo(v[it][i].y) + bf_hi(v[it][i].y));
                    s1 += (bf_lo(v[it][i].z) + bf_hi(v[it][i].z)) + (bf_lo(v[it][i].w) + bf_hi(v[it][i].w));
                }
                float s = s0 + s1;
                s += __shfl_xor_sync(0xffffffffu, s, 1);
                s += __shfl_xor_sync(0xffffffffu, s, 2);
                s += __shfl_xor_sync(0xffffffffu, s, 4);
                if (it == 0 && tid == 0) TL(0, 3);
                const float mean = s * (1.0f / D_);
                float q0 = 0.f, q1 = 0.f;
#pragma unroll
                for (int i = 0; i < 7; i++) {
                    const uint32_t w[4] = {v[it][i].x, v[it][i].y, v[it][i].z, v[it][i].w};
#pragma unroll
                    for (int c = 0; c < 4; c++) {
                        const float d0 = bf_lo(w[c]) - mean, d1 = bf_hi(w[c]) - mean;
                        q0 = fmaf(d0, d0, q0);
                        q1 = fmaf(d1, d1, q1);
                    }
                }
                float q = q0 + q1;
                q += __shfl_xor_sync(0xffffffffu, q, 1);
                q += __shfl_xor_sync(0xffffffffu, q, 2);
                q += __shfl_xor_sync(0xffffffffu, q, 4);
                const float var = rbf(q * (1.0f / D_));
                const float den = rbf(sqrtf(rbf(var + 1e-5f)));
                const float rinv = 1.0f / den;
                const float rhi = rbf(rinv);
                const uint32_t m2 = pack_bf16(mean, mean), rhi2 = pack_bf16(rhi, rhi), rlo2 = pack_bf16(rinv - rhi, rinv - rhi);
                const uint32_t dst = sb + S1_XN + row * 128 + ((l8 ^ (row & 7)) << 4);
#pragma unroll
                for (int i = 0; i < 7; i++) {
                    const uint32_t w[4] = {v[it][i].x, v[it][i].y, v[it][i].z, v[it][i].w};
                    uint32_t o[4];
#pragma unroll
                    for (int c = 0; c < 4; c++) {
                        const uint32_t xc = hsub2(w[c], m2);
                        o[c] = hfma2(xc, rhi2, hmul2(xc, rlo2));
                    }
                    asm volatile("st.shared.v4.b32 [%0], {%1, %2, %3, %4};" ::"r"(dst + i * 16384), "r"(o[0]), "r"(o[1]), "r"(o[2]), "r"(o[3]) : "memory");
                }
            }
        }
        fence_async();
        __syncthreads();
        if (tid == 0) TL(0, 2);
    }

    if (warp >= 8) {
        asm volatile("setmaxnreg.dec.sync.aligned.u32 40;");
        if (warp == 8) {
            if (lane == 0) {
                int st = 0;
                uint32_t ph = 0;
                for (int p = 1; p < npass; p++) {
                    const int slab = pass_slab(j, p);
                    for (int kb = 0; kb < 7; kb++) {
                        mbar_wait(sb + BAR_E1 + 8 * st, ph);
                        const uint32_t fb = sb + BAR_F1 + 8 * st;
                        mbar_expect(fb, 16384);
                        tma_load_mc(sb + S1_B + st * 16384 + rank * 8192, rank ? &tm.wu : &tm.wg, fb, slab * 64, kb * 64);
                        if (++st == S1_STAGES) { st = 0; ph ^= 1; }
                    }
                }
                if (part < 3) {
                    mbar_wait(sb + BAR_S1DONE, 0);
                    TL(0, 24);
                    st = 0; ph = 1;
                    if (part < 2) {
                        const CUtensorMap* ma = part ? &tm.sim : &tm.sre;
                        for (int g = 0; g < 32; g++) {
                            mbar_wait(sb + BAR_E2 + 8 * st, ph);
                            const uint32_t dst = sb + st * Y_STAGE;
                            const uint32_t fb = sb + BAR_F2 + 8 * st;
                            mbar_expect(fb, Y_STAGE);
                            tma_load(dst, ma, fb, g * 64, rb * 128);
                            dep_wait(sb, (g >> 1) + 1);
                            tma_load_mc(dst + 16384 + rank * 14336, &tm.abT, fb, g * 64, part * 448 + n * 224 + rank * 112);
                            if (++st == Y_STAGES) { st = 0; ph ^= 1; }
                        }
                    } else {
                        for (int g = 0; g < 28; g++) {
                            mbar_wait(sb + BAR_E2 + 8 * st, ph);
                            const uint32_t dst = sb + st * F_STAGE;
                            const uint32_t fb = sb + BAR_F2 + 8 * st;
                            mbar_expect(fb, F_STAGE);
                            tma_load_mc(dst + 16384 + (2 * rank) * 8192, &tm.wd, fb, n * 224 + (2 * rank) * 64, g * 64);
                            tma_load_mc(dst + 16384 + (2 * rank + 1) * 8192, &tm.wd, fb, n * 224 + (2 * rank + 1) * 64, g * 64);
                            dep_wait(sb, g + 1);
                            tma_load(dst, &tm.h, fb, g * 64, rb * 128);
                            if (++st == F_STAGES) { st = 0; ph ^= 1; }
                        }
                    }
                }
            }
        } else if (warp == 9) {
            if (part < 3) {
                if (part < 2 && lane < 16) {
                    tma_prefetch(part ? &tm.sim : &tm.sre, (2 * lane + n) * 64, rb * 128);
                }
                const int ndep = part < 2 ? 16 : 29;
                const unsigned int epoch = *(volatile unsigned int*)&g_fl.done / gridDim.x + 1;
                const unsigned int* f = part < 2 ? &g_fl.ab[lane & 15] : (lane < 28 ? &g_fl.h[rb * 28 + lane] : &g_fl.y[rb * 2 + n]);
                const unsigned int target = (part < 2 ? 7 : (lane < 28 ? 1 : 16)) * epoch;
                bool ok = lane >= ndep;
                int published = 0;
                for (int spins = 0; published < ndep && spins < (1 << 22); spins++) {
                    if (!ok) {
                        unsigned int v;
                        asm volatile("ld.acquire.gpu.global.u32 %0, [%1];" : "=r"(v) : "l"(f) : "memory");
                        ok = (int)(v - target) >= 0;
                    }
                    const unsigned int m = __ballot_sync(0xffffffffu, ok);
                    const int cnt = min(__ffs(~m) - 1, ndep);
                    if (m == 0xffffffffu || cnt > published) {
                        published = (m == 0xffffffffu) ? ndep : cnt;
                        fence_async_all();
                        __syncwarp();
                        if (lane == 0) asm volatile("st.release.cta.shared.u32 [%0], %1;" ::"r"(sb + DEP_CNT), "r"(published) : "memory");
                    }
                }
                if (published < ndep && lane == 0)
                    asm volatile("st.release.cta.shared.u32 [%0], %1;" ::"r"(sb + DEP_CNT), "r"(ndep) : "memory");
            }
        } else {
            if (lane == 0) {
                const int w = warp - 10;
                uint32_t ph = 0;
                for (int p = w; p < npass; p += 2) {
                    const int slab = pass_slab(j, p);
                    mbar_wait(sb + BAR_PUB + 8 * w, ph);
                    ph ^= 1;
                    __threadfence();
                    flag_add(slab >= 0 ? &g_fl.h[rb * 28 + slab] : &g_fl.ab[rb]);
                }
            }
        }
        __syncwarp();
    } else {
        asm volatile("setmaxnreg.inc.sync.aligned.u32 232;");
        const int wg = warp >> 2, wl = warp & 3, wtid = tid & 127;
        const int qd = lane & 3;
        {
            float acc[2][64];
            for (int p = wg; p < npass; p += 2) {
                const int slab = pass_slab(j, p);
                if (p > 0) bar_sync(4 + (p & 1), 256);
                const int handoff = (p + 1 < npass) ? 4 + ((p + 1) & 1) : 0;
                if (slab >= 0) s1_mainloop<1>(acc, sb, p, lane, handoff);
                else s1_mainloop<0>(acc, sb, p, lane, handoff);
                if (p + 2 >= npass && part < 3 && lane == 0) mbar_arrive_both(sb + BAR_S1DONE);
                if (wtid == 0 && p < 4) TL(0, 4 + p);

                if (slab >= 0) {
                    __nv_bfloat16* dst = g_h + (size_t)(rb * 128 + wl * 16 + (lane >> 2)) * F_ + slab * 64 + qd * 8;
#pragma unroll
                    for (int mh = 0; mh < 2; mh++) {
#pragma unroll
                        for (int hh = 0; hh < 2; hh++) {
#pragma unroll
                            for (int g4 = 0; g4 < 2; g4++) {
                                uint32_t r[4];
#pragma unroll
                                for (int t = 0; t < 4; t++) {
                                    const int o = (g4 * 4 + t) * 4 + hh * 2;
                                    const uint32_t g2 = pack_bf16(acc[mh][o], acc[mh][o + 1]);
                                    const uint32_t u2 = pack_bf16(acc[mh][32 + o], acc[mh][32 + o + 1]);
                                    const uint32_t a2 = pack_bf16(gelu_tanh(bf_lo(g2)), gelu_tanh(bf_hi(g2)));
                                    r[t] = hmul2(a2, u2);
                                }
                                quad_transpose(r, qd);
                                __stcg(reinterpret_cast<uint4*>(dst + (size_t)(mh * 64 + hh * 8) * F_ + g4 * 32), make_uint4(r[0], r[1], r[2], r[3]));
                            }
                        }
                    }
                } else {
                    __nv_bfloat16* dst = g_abT + (size_t)(j * 128 + wl * 16 + (lane >> 2)) * ABP + rb * 128 + qd * 8;
#pragma unroll
                    for (int mh = 0; mh < 2; mh++) {
#pragma unroll
                        for (int hh = 0; hh < 2; hh++) {
#pragma unroll
                            for (int g4 = 0; g4 < 4; g4++) {
                                uint32_t r[4];
#pragma unroll
                                for (int t = 0; t < 4; t++) {
                                    const int o = (g4 * 4 + t) * 4 + hh * 2;
                                    r[t] = pack_bf16(acc[mh][o], acc[mh][o + 1]);
                                }
                                quad_transpose(r, qd);
                                __stcg(reinterpret_cast<uint4*>(dst + (size_t)(mh * 64 + hh * 8) * ABP + g4 * 32), make_uint4(r[0], r[1], r[2], r[3]));
                            }
                        }
                    }
                }
                __syncwarp();
                if (lane == 0) mbar_arrive(sb + BAR_PUB + 8 * wg);
                if (wtid == 0 && p < 4) TL(0, 10 + p);
            }
        }
        if (wtid == 0) TL(0, 20 + wg);
        if (part < 3) {
            {
                float acc[112];
                const size_t base = (size_t)(rb * 128 + wg * 64 + wl * 16 + (lane >> 2)) * D_ + n * 224 + qd * 8;
                if (part < 2) {
                    s2_mainloop<0>(acc, sb, wg, lane);
                    if (tid == 0) TL(0, 25);
                    uint4* dst = g_y + (size_t)((part * 32 + rb * 2 + n) * 14) * 256 + tid;
#pragma unroll
                    for (int i = 0; i < 14; i++)
                        __stcg(dst + i * 256, make_uint4(pack_bf16(acc[8 * i], acc[8 * i + 1]), pack_bf16(acc[8 * i + 2], acc[8 * i + 3]),
                                                         pack_bf16(acc[8 * i + 4], acc[8 * i + 5]), pack_bf16(acc[8 * i + 6], acc[8 * i + 7])));
                    __threadfence();
                    __syncwarp();
                    if (lane == 0) flag_add(&g_fl.y[rb * 2 + n]);
                } else {
                    uint4 xv[14];
#pragma unroll
                    for (int i = 0; i < 14; i++)
                        xv[i] = __ldg(reinterpret_cast<const uint4*>(pt.x + base + (i / 7) * 8 * D_ + (i % 7) * 32));
                    s2_mainloop<1>(acc, sb, wg, lane);
                    if (tid == 0) TL(0, 25);
                    dep_wait(sb, 29);
                    if (tid == 0) TL(0, 26);
                    const uint4* ysrc = g_y + (size_t)((rb * 2 + n) * 14) * 256 + tid;
                    uint4 yr[14], yi[14];
#pragma unroll
                    for (int i = 0; i < 14; i++) yr[i] = __ldcg(ysrc + i * 256);
                    uint32_t sg[56];
#pragma unroll
                    for (int i = 0; i < 56; i++) {
                        const uint32_t f2 = pack_bf16(acc[2 * i], acc[2 * i + 1]);
                        sg[i] = pack_bf16(silu(bf_lo(f2)), silu(bf_hi(f2)));
                    }
#pragma unroll
                    for (int i = 0; i < 14; i++) yi[i] = __ldcg(ysrc + (32 * 14 + i) * 256);
#pragma unroll
                    for (int i = 0; i < 14; i++) {
                        sg[4 * i + 0] = hmul2(hsub2(yr[i].x, yi[i].x), sg[4 * i + 0]);
                        sg[4 * i + 1] = hmul2(hsub2(yr[i].y, yi[i].y), sg[4 * i + 1]);
                        sg[4 * i + 2] = hmul2(hsub2(yr[i].z, yi[i].z), sg[4 * i + 2]);
                        sg[4 * i + 3] = hmul2(hsub2(yr[i].w, yi[i].w), sg[4 * i + 3]);
                    }
#pragma unroll
                    for (int hh = 0; hh < 2; hh++) {
#pragma unroll
                        for (int g4 = 0; g4 < 7; g4++) {
                            uint32_t r[4];
#pragma unroll
                            for (int t = 0; t < 4; t++) r[t] = sg[(g4 * 4 + t) * 2 + hh];
                            quad_transpose(r, qd);
                            const uint4 xx = xv[hh * 7 + g4];
                            *reinterpret_cast<uint4*>(pt.out + base + hh * 8 * D_ + g4 * 32) =
                                make_uint4(hadd2(xx.x, r[0]), hadd2(xx.y, r[1]), hadd2(xx.z, r[2]), hadd2(xx.w, r[3]));
                        }
                    }
                }
            }
        }
    }
    if (tid == 0) TL(0, 29);
    __syncthreads();
    if (tid == 0) {
        TL(0, 30);
        atomicAdd(&g_fl.done, 1u);
    }
}

typedef CUresult (*EncFn)(CUtensorMap*, CUtensorMapDataType, cuuint32_t, void*, const cuuint64_t*, const cuuint64_t*,
                          const cuuint32_t*, const cuuint32_t*, CUtensorMapInterleave, CUtensorMapSwizzle,
                          CUtensorMapL2promotion, CUtensorMapFloatOOBfill);

void make_map(EncFn enc, CUtensorMap* m, const void* ptr, int rows, int cols, int box_rows, int box_cols, int pitch = 0) {
    const bool swz = true;
    cuuint64_t gd[2] = {(cuuint64_t)cols, (cuuint64_t)rows};
    cuuint64_t gs[1] = {(cuuint64_t)(pitch ? pitch : cols) * 2};
    cuuint32_t bx[2] = {(cuuint32_t)box_cols, (cuuint32_t)box_rows};
    cuuint32_t es[2] = {1, 1};
    enc(m, CU_TENSOR_MAP_DATA_TYPE_BFLOAT16, 2, const_cast<void*>(ptr), gd, gs, bx, es, CU_TENSOR_MAP_INTERLEAVE_NONE,
        swz ? CU_TENSOR_MAP_SWIZZLE_128B : CU_TENSOR_MAP_SWIZZLE_NONE, CU_TENSOR_MAP_L2_PROMOTION_L2_128B,
        CU_TENSOR_MAP_FLOAT_OOB_FILL_NONE);
}

}

extern "C" void kernel_launch(void* const* d_in, const int* in_sizes, int n_in, void* d_out, int out_size) {
    Ptrs pt;
    pt.x = (const __nv_bfloat16*)d_in[0];
    pt.hre = (const __nv_bfloat16*)d_in[3];
    pt.him = (const __nv_bfloat16*)d_in[4];
    pt.wg = (const __nv_bfloat16*)d_in[6];
    pt.wu = (const __nv_bfloat16*)d_in[7];
    pt.wd = (const __nv_bfloat16*)d_in[8];
    pt.out = (__nv_bfloat16*)d_out;

    void* fn = nullptr;
    cudaDriverEntryPointQueryResult qr;
    cudaGetDriverEntryPoint("cuTensorMapEncodeTiled", &fn, cudaEnableDefault, &qr);
    EncFn enc = (EncFn)fn;
    void *p_abT, *p_h;
    cudaGetSymbolAddress(&p_abT, g_abT);
    cudaGetSymbolAddress(&p_h, g_h);

    Maps tm;
    make_map(enc, &tm.wg, d_in[6], D_, F_, 64, 64);
    make_map(enc, &tm.wu, d_in[7], D_, F_, 64, 64);
    make_map(enc, &tm.hre, d_in[3], D_, D_, 64, 64);
    make_map(enc, &tm.him, d_in[4], D_, D_, 64, 64);
    make_map(enc, &tm.h, p_h, S_, F_, 128, 64);
    make_map(enc, &tm.abT, p_abT, 896, S_, 112, 64, ABP);
    make_map(enc, &tm.sre, d_in[1], S_, S_, 128, 64);
    make_map(enc, &tm.sim, d_in[2], S_, S_, 128, 64);
    make_map(enc, &tm.wd, d_in[8], F_, D_, 64, 64);

    cudaFuncSetAttribute(fused_kernel, cudaFuncAttributeMaxDynamicSharedMemorySize, SMEM_BYTES);

    cudaLaunchAttribute at[1];
    at[0].id = cudaLaunchAttributeClusterDimension;
    at[0].val.clusterDim.x = 2; at[0].val.clusterDim.y = 1; at[0].val.clusterDim.z = 1;
    cudaLaunchConfig_t cfg = {};
    cfg.gridDim = dim3(128); cfg.blockDim = dim3(384); cfg.stream = cudaStreamPerThread;
    cfg.attrs = at; cfg.numAttrs = 1;
    cfg.dynamicSmemBytes = SMEM_BYTES;
    cudaLaunchKernelEx(&cfg, fused_kernel, pt, tm);
}
```

```cpp
#include <cuda_runtime.h>
#include <cuda_bf16.h>
#include <cuda.h>
#include <stdint.h>

namespace {

constexpr int S_ = 2048, D_ = 448, F_ = 1792;

constexpr int ABP = 2048 + 64;
__device__ __align__(1024) __nv_bfloat16 g_abT[896 * ABP];
__device__ __align__(1024) __nv_bfloat16 g_h[2048 * 1792];
__device__ __align__(1024) uint4 g_y[2 * 32 * 14 * 256];
struct Flags {
    unsigned int ab[16];
    unsigned int h[16 * 28];
    unsigned int y[32];
    unsigned int done;
};
__device__ Flags g_fl;

#define TL(k, i) do {} while (0)
__device__ __forceinline__ uint32_t s2u(const void* p) { return (uint32_t)__cvta_generic_to_shared(p); }
__device__ __forceinline__ void mbar_init(uint32_t b, int c) {
    asm volatile("mbarrier.init.shared::cta.b64 [%0], %1;" ::"r"(b), "r"(c));
}
__device__ __forceinline__ void mbar_expect(uint32_t b, uint32_t bytes) {
    asm volatile("mbarrier.arrive.expect_tx.shared::cta.b64 _, [%0], %1;" ::"r"(b), "r"(bytes) : "memory");
}
__device__ __forceinline__ void mbar_wait(uint32_t b, uint32_t ph) {
    uint32_t ok;
    do {
        asm volatile("{\n.reg .pred p;\nmbarrier.try_wait.parity.shared::cta.b64 p, [%1], %2;\nselp.u32 %0, 1, 0, p;\n}"
                     : "=r"(ok) : "r"(b), "r"(ph) : "memory");
    } while (!ok);
}
__device__ __forceinline__ void mbar_arrive_both(uint32_t b) {
    asm volatile("{\n.reg .b32 r0, r1;\n"
                 "mapa.shared::cluster.u32 r0, %0, 0;\n"
                 "mapa.shared::cluster.u32 r1, %0, 1;\n"
                 "mbarrier.arrive.shared::cluster.b64 _, [r0];\n"
                 "mbarrier.arrive.shared::cluster.b64 _, [r1];\n}"
                 ::"r"(b) : "memory");
}
__device__ __forceinline__ void tma_load(uint32_t dst, const CUtensorMap* m, uint32_t bar, int c0, int c1) {
    asm volatile("cp.async.bulk.tensor.2d.shared::cluster.global.mbarrier::complete_tx::bytes [%0], [%1, {%3, %4}], [%2];"
                 ::"r"(dst), "l"(m), "r"(bar), "r"(c0), "r"(c1) : "memory");
}
__device__ __forceinline__ void tma_load_mc(uint32_t dst, const CUtensorMap* m, uint32_t bar, int c0, int c1) {
    asm volatile("cp.async.bulk.tensor.2d.shared::cluster.global.mbarrier::complete_tx::bytes.multicast::cluster [%0], [%1, {%3, %4}], [%2], %5;"
                 ::"r"(dst), "l"(m), "r"(bar), "r"(c0), "r"(c1), "h"((uint16_t)3) : "memory");
}
__device__ __forceinline__ void tma_store(const CUtensorMap* m, uint32_t src, int c0, int c1) {
    asm volatile("cp.async.bulk.tensor.2d.global.shared::cta.bulk_group [%0, {%2, %3}], [%1];"
                 ::"l"(m), "r"(src), "r"(c0), "r"(c1) : "memory");
}
__device__ __forceinline__ void bulk_commit() { asm volatile("cp.async.bulk.commit_group;" ::: "memory"); }
__device__ __forceinline__ void bulk_wait_read0() { asm volatile("cp.async.bulk.wait_group.read 0;" ::: "memory"); }
__device__ __forceinline__ void bulk_wait0() { asm volatile("cp.async.bulk.wait_group 0;" ::: "memory"); }
__device__ __forceinline__ void fence_async() { asm volatile("fence.proxy.async.shared::cta;" ::: "memory"); }
__device__ __forceinline__ void fence_async_all() { asm volatile("fence.proxy.async;" ::: "memory"); }
__device__ __forceinline__ void cluster_sync() {
    asm volatile("barrier.cluster.arrive.release.aligned;\nbarrier.cluster.wait.acquire.aligned;" ::: "memory");
}
__device__ __forceinline__ void bar_sync(int id, int n) { asm volatile("bar.sync %0, %1;" ::"r"(id), "r"(n) : "memory"); }
__device__ __forceinline__ void wg_arrive() { asm volatile("wgmma.fence.sync.aligned;" ::: "memory"); }
__device__ __forceinline__ void wg_commit() { asm volatile("wgmma.commit_group.sync.aligned;" ::: "memory"); }
template <int N> __device__ __forceinline__ void wg_wait() { asm volatile("wgmma.wait_group.sync.aligned %0;" ::"n"(N) : "memory"); }
__device__ __forceinline__ void stmat4(uint32_t a, uint32_t r0, uint32_t r1, uint32_t r2, uint32_t r3) {
    asm volatile("stmatrix.sync.aligned.m8n8.x4.shared.b16 [%0], {%1, %2, %3, %4};" ::"r"(a), "r"(r0), "r"(r1), "r"(r2), "r"(r3) : "memory");
}
__device__ __forceinline__ void stmat4t(uint32_t a, uint32_t r0, uint32_t r1, uint32_t r2, uint32_t r3) {
    asm volatile("stmatrix.sync.aligned.m8n8.x4.trans.shared.b16 [%0], {%1, %2, %3, %4};" ::"r"(a), "r"(r0), "r"(r1), "r"(r2), "r"(r3) : "memory");
}
__device__ __forceinline__ void ldmat4(uint32_t a, uint32_t (&r)[4]) {
    asm volatile("ldmatrix.sync.aligned.m8n8.x4.shared.b16 {%0, %1, %2, %3}, [%4];"
                 : "=r"(r[0]), "=r"(r[1]), "=r"(r[2]), "=r"(r[3]) : "r"(a) : "memory");
}
__device__ __forceinline__ void flag_add(unsigned int* f) {
    asm volatile("red.release.gpu.global.add.u32 [%0], 1;" ::"l"(f) : "memory");
}
__device__ __forceinline__ void flag_wait(const unsigned int* f, unsigned int target) {
    unsigned int v;
    int spins = 0;
    while (true) {
        asm volatile("ld.acquire.gpu.global.u32 %0, [%1];" : "=r"(v) : "l"(f) : "memory");
        if ((int)(v - target) >= 0 || ++spins > (1 << 22)) break;
    }
}
__device__ __forceinline__ void quad_transpose(uint32_t (&r)[4], int q) {
    const bool o1 = q & 1, o2 = q & 2;
    uint32_t a = o1 ? r[0] : r[1], b = o1 ? r[2] : r[3];
    a = __shfl_xor_sync(0xffffffffu, a, 1);
    b = __shfl_xor_sync(0xffffffffu, b, 1);
    if (o1) { r[0] = a; r[2] = b; } else { r[1] = a; r[3] = b; }
    a = o2 ? r[0] : r[2]; b = o2 ? r[1] : r[3];
    a = __shfl_xor_sync(0xffffffffu, a, 2);
    b = __shfl_xor_sync(0xffffffffu, b, 2);
    if (o2) { r[0] = a; r[1] = b; } else { r[2] = a; r[3] = b; }
}
__device__ __forceinline__ uint32_t movmat_t(uint32_t v) {
    uint32_t r;
    asm volatile("movmatrix.sync.aligned.m8n8.trans.b16 %0, %1;" : "=r"(r) : "r"(v));
    return r;
}
__device__ __forceinline__ uint64_t mkdesc(uint32_t addr, uint32_t lbo, uint32_t sbo) {
    return (uint64_t)((addr & 0x3FFFF) >> 4) | ((uint64_t)(lbo >> 4) << 16) | ((uint64_t)(sbo >> 4) << 32) | (1ull << 62);
}
__device__ __forceinline__ uint32_t pack_bf16(float lo, float hi) {
    uint32_t r;
    asm("cvt.rn.bf16x2.f32 %0, %1, %2;" : "=r"(r) : "f"(hi), "f"(lo));
    return r;
}
__device__ __forceinline__ uint32_t hsub2(uint32_t a, uint32_t b) { uint32_t r; asm("sub.rn.bf16x2 %0, %1, %2;" : "=r"(r) : "r"(a), "r"(b)); return r; }
__device__ __forceinline__ uint32_t hadd2(uint32_t a, uint32_t b) { uint32_t r; asm("add.rn.bf16x2 %0, %1, %2;" : "=r"(r) : "r"(a), "r"(b)); return r; }
__device__ __forceinline__ uint32_t hmul2(uint32_t a, uint32_t b) { uint32_t r; asm("mul.rn.bf16x2 %0, %1, %2;" : "=r"(r) : "r"(a), "r"(b)); return r; }
__device__ __forceinline__ uint32_t hfma2(uint32_t a, uint32_t b, uint32_t c) { uint32_t r; asm("fma.rn.bf16x2 %0, %1, %2, %3;" : "=r"(r) : "r"(a), "r"(b), "r"(c)); return r; }
__device__ __forceinline__ float bf_lo(uint32_t u) { return __uint_as_float(u << 16); }
__device__ __forceinline__ float bf_hi(uint32_t u) { return __uint_as_float(u & 0xffff0000u); }
__device__ __forceinline__ float rbf(float v) { return __bfloat162float(__float2bfloat16_rn(v)); }
__device__ __forceinline__ float tanh_fast(float x) { float r; asm("tanh.approx.f32 %0, %1;" : "=f"(r) : "f"(x)); return r; }
__device__ __forceinline__ float gelu_tanh(float x) {
    float u = x * fmaf(x * x, 0.0356774081f, 0.7978845608f);
    float hx = 0.5f * x;
    return fmaf(hx, tanh_fast(u), hx);
}
__device__ __forceinline__ float silu(float f) { const float hf = 0.5f * f; return fmaf(hf, tanh_fast(hf), hf); }

template <int TB>
__device__ __forceinline__ void wgmma_n128(float (&d)[64], uint64_t da, uint64_t db, int scaleD) {
    asm volatile("{\n.reg .pred p;\nsetp.ne.b32 p, %66, 0;\n"
        "wgmma.mma_async.sync.aligned.m64n128k16.f32.bf16.bf16 {%0, %1, %2, %3, %4, %5, %6, %7, %8, %9, %10, %11, %12, %13, %14, %15, %16, %17, %18, %19, %20, %21, %22, %23, %24, %25, %26, %27, %28, %29, %30, %31, %32, %33, %34, %35, %36, %37, %38, %39, %40, %41, %42, %43, %44, %45, %46, %47, %48, %49, %50, %51, %52, %53, %54, %55, %56, %57, %58, %59, %60, %61, %62, %63}, %64, %65, p, 1, 1, 0, %67;\n}\n"
        : "+f"(d[0]), "+f"(d[1]), "+f"(d[2]), "+f"(d[3]), "+f"(d[4]), "+f"(d[5]), "+f"(d[6]), "+f"(d[7]), "+f"(d[8]), "+f"(d[9]), "+f"(d[10]), "+f"(d[11]), "+f"(d[12]), "+f"(d[13]), "+f"(d[14]), "+f"(d[15]), "+f"(d[16]), "+f"(d[17]), "+f"(d[18]), "+f"(d[19]), "+f"(d[20]), "+f"(d[21]), "+f"(d[22]), "+f"(d[23]), "+f"(d[24]), "+f"(d[25]), "+f"(d[26]), "+f"(d[27]), "+f"(d[28]), "+f"(d[29]), "+f"(d[30]), "+f"(d[31]), "+f"(d[32]), "+f"(d[33]), "+f"(d[34]), "+f"(d[35]), "+f"(d[36]), "+f"(d[37]), "+f"(d[38]), "+f"(d[39]), "+f"(d[40]), "+f"(d[41]), "+f"(d[42]), "+f"(d[43]), "+f"(d[44]), "+f"(d[45]), "+f"(d[46]), "+f"(d[47]), "+f"(d[48]), "+f"(d[49]), "+f"(d[50]), "+f"(d[51]), "+f"(d[52]), "+f"(d[53]), "+f"(d[54]), "+f"(d[55]), "+f"(d[56]), "+f"(d[57]), "+f"(d[58]), "+f"(d[59]), "+f"(d[60]), "+f"(d[61]), "+f"(d[62]), "+f"(d[63])
        : "l"(da), "l"(db), "r"(scaleD), "n"(TB));
}
template <int TB>
__device__ __forceinline__ void wgmma_n224(float (&d)[112], uint64_t da, uint64_t db, int scaleD) {
    asm volatile("{\n.reg .pred p;\nsetp.ne.b32 p, %114, 0;\n"
        "wgmma.mma_async.sync.aligned.m64n224k16.f32.bf16.bf16 {%0, %1, %2, %3, %4, %5, %6, %7, %8, %9, %10, %11, %12, %13, %14, %15, %16, %17, %18, %19, %20, %21, %22, %23, %24, %25, %26, %27, %28, %29, %30, %31, %32, %33, %34, %35, %36, %37, %38, %39, %40, %41, %42, %43, %44, %45, %46, %47, %48, %49, %50, %51, %52, %53, %54, %55, %56, %57, %58, %59, %60, %61, %62, %63, %64, %65, %66, %67, %68, %69, %70, %71, %72, %73, %74, %75, %76, %77, %78, %79, %80, %81, %82, %83, %84, %85, %86, %87, %88, %89, %90, %91, %92, %93, %94, %95, %96, %97, %98, %99, %100, %101, %102, %103, %104, %105, %106, %107, %108, %109, %110, %111}, %112, %113, p, 1, 1, 0, %115;\n}\n"
        : "+f"(d[0]), "+f"(d[1]), "+f"(d[2]), "+f"(d[3]), "+f"(d[4]), "+f"(d[5]), "+f"(d[6]), "+f"(d[7]), "+f"(d[8]), "+f"(d[9]), "+f"(d[10]), "+f"(d[11]), "+f"(d[12]), "+f"(d[13]), "+f"(d[14]), "+f"(d[15]), "+f"(d[16]), "+f"(d[17]), "+f"(d[18]), "+f"(d[19]), "+f"(d[20]), "+f"(d[21]), "+f"(d[22]), "+f"(d[23]), "+f"(d[24]), "+f"(d[25]), "+f"(d[26]), "+f"(d[27]), "+f"(d[28]), "+f"(d[29]), "+f"(d[30]), "+f"(d[31]), "+f"(d[32]), "+f"(d[33]), "+f"(d[34]), "+f"(d[35]), "+f"(d[36]), "+f"(d[37]), "+f"(d[38]), "+f"(d[39]), "+f"(d[40]), "+f"(d[41]), "+f"(d[42]), "+f"(d[43]), "+f"(d[44]), "+f"(d[45]), "+f"(d[46]), "+f"(d[47]), "+f"(d[48]), "+f"(d[49]), "+f"(d[50]), "+f"(d[51]), "+f"(d[52]), "+f"(d[53]), "+f"(d[54]), "+f"(d[55]), "+f"(d[56]), "+f"(d[57]), "+f"(d[58]), "+f"(d[59]), "+f"(d[60]), "+f"(d[61]), "+f"(d[62]), "+f"(d[63]), "+f"(d[64]), "+f"(d[65]), "+f"(d[66]), "+f"(d[67]), "+f"(d[68]), "+f"(d[69]), "+f"(d[70]), "+f"(d[71]), "+f"(d[72]), "+f"(d[73]), "+f"(d[74]), "+f"(d[75]), "+f"(d[76]), "+f"(d[77]), "+f"(d[78]), "+f"(d[79]), "+f"(d[80]), "+f"(d[81]), "+f"(d[82]), "+f"(d[83]), "+f"(d[84]), "+f"(d[85]), "+f"(d[86]), "+f"(d[87]), "+f"(d[88]), "+f"(d[89]), "+f"(d[90]), "+f"(d[91]), "+f"(d[92]), "+f"(d[93]), "+f"(d[94]), "+f"(d[95]), "+f"(d[96]), "+f"(d[97]), "+f"(d[98]), "+f"(d[99]), "+f"(d[100]), "+f"(d[101]), "+f"(d[102]), "+f"(d[103]), "+f"(d[104]), "+f"(d[105]), "+f"(d[106]), "+f"(d[107]), "+f"(d[108]), "+f"(d[109]), "+f"(d[110]), "+f"(d[111])
        : "l"(da), "l"(db), "r"(scaleD), "n"(TB));
}

constexpr int S1_STAGES = 6;
constexpr int S1_XN = 0;
constexpr int S1_B = 7 * 16384;
constexpr int STG = S1_B + S1_STAGES * 16384;
constexpr int Y_STAGES = 4, Y_STAGE = 45056;
constexpr int F_STAGES = 4, F_STAGE = 49152;
constexpr int BAR = STG + 16384;
constexpr int BAR_F1 = BAR, BAR_E1 = BAR + 56, BAR_F2 = BAR + 112, BAR_E2 = BAR + 152, BAR_S1DONE = BAR + 192;
constexpr int BAR_SF = BAR + 208;
constexpr int SE_CNT = BAR + 216;
constexpr int DEP_CNT = BAR + 200;
constexpr int SMEM_BYTES = BAR + 256 + 1024;
constexpr int TPITCH = 464;

__device__ __forceinline__ int n_passes(int j) { return j < 4 ? 2 : (j < 6 ? 4 : (j == 6 ? 10 : 9)); }
__device__ __forceinline__ int pass_slab(int j, int p) {
    if (p == 0) return j < 7 ? -1 : 0;
    if (p == 1) return 1 + j;
    if (p < 4) return 4 * p - 3 + j;
    return 17 + 2 * (p - 4) + (j - 6);
}

template <int TB>
__device__ __forceinline__ void s1_mainloop(float (&acc)[2][64], uint32_t sb, int p, int lane, int handoff) {
    int st = (p * 7) % S1_STAGES;
    uint32_t ph = ((p * 7) / S1_STAGES) & 1;
    int prev = 0;
    uint64_t dx = mkdesc(sb + S1_XN, 16, 1024);
    const uint64_t dw0 = TB ? mkdesc(sb + S1_B, 8192, 1024) : mkdesc(sb + S1_B, 16, 1024);
    const int nrel = lane == 0 ? (handoff ? 7 : 7 - S1_STAGES) : 0;
#pragma unroll 1
    for (int kb = 0; kb < 7; kb++) {
        mbar_wait(sb + BAR_F1 + 8 * st, ph);
        if (kb == 6 && handoff) asm volatile("bar.arrive %0, 256;" ::"r"(handoff) : "memory");
        const uint64_t dw = dw0 + st * 1024;
        wg_arrive();
#pragma unroll
        for (int s = 0; s < 4; s++) {
            if (TB) {
                wgmma_n128<1>(acc[0], dx + s * 2, dw + s * 128, kb | s);
                wgmma_n128<1>(acc[1], dx + 512 + s * 2, dw + s * 128, kb | s);
            } else {
                wgmma_n128<0>(acc[0], dw + s * 2, dx + s * 2, kb | s);
                wgmma_n128<0>(acc[1], dw + 512 + s * 2, dx + s * 2, kb | s);
            }
        }
        wg_commit();
        wg_wait<1>();
        if (kb > 0 && kb <= nrel) mbar_arrive_both(sb + BAR_E1 + 8 * prev);
        prev = st;
        dx += 1024;
        if (++st == S1_STAGES) { st = 0; ph ^= 1; }
    }
    wg_wait<0>();
    if (nrel == 7) mbar_arrive_both(sb + BAR_E1 + 8 * prev);
}

template <int TB>
__device__ __forceinline__ void s2_mainloop(float (&acc)[112], uint32_t sb, int wg, int lane) {
    constexpr int NST = TB ? F_STAGES : Y_STAGES, SSZ = TB ? F_STAGE : Y_STAGE, NKB = TB ? 28 : 32;
    int st = 0;
    uint32_t ph = 0;
    int prev = 0;
    const uint64_t da0 = mkdesc(sb + wg * 8192, 16, 1024);
    const uint64_t db0 = TB ? mkdesc(sb + 16384, 8192, 1024) : mkdesc(sb + 16384, 16, 1024);
#pragma unroll 1
    for (int i = 0; i < NKB; i++) {
        mbar_wait(sb + BAR_F2 + 8 * st, ph);
        const uint64_t da = da0 + st * (SSZ / 16), db = db0 + st * (SSZ / 16);
        wg_arrive();
#pragma unroll
        for (int s = 0; s < 4; s++) wgmma_n224<TB>(acc, da + s * 2, db + s * (TB ? 128 : 2), i | s);
        wg_commit();
        wg_wait<1>();
        if (i > 0 && i <= NKB - NST && lane == 0) mbar_arrive_both(sb + BAR_E2 + 8 * prev);
        prev = st;
        if (++st == NST) { st = 0; ph ^= 1; }
    }
    wg_wait<0>();
}

struct Maps {
    CUtensorMap wg, wu, hre, him, h, abT, abT_st, sre, sim, wd;
};
struct Ptrs {
    const __nv_bfloat16 *x, *hre, *him, *wg, *wu, *wd;
    __nv_bfloat16* out;
};
__device__ __forceinline__ void mbar_arrive(uint32_t b) {
    asm volatile("mbarrier.arrive.shared::cta.b64 _, [%0];" ::"r"(b) : "memory");
}
__device__ __forceinline__ void l2_prefetch(const void* p, uint32_t bytes) {
    asm volatile("cp.async.bulk.prefetch.L2.global [%0], %1;" ::"l"(p), "r"(bytes) : "memory");
}
__device__ __forceinline__ void tma_prefetch(const CUtensorMap* m, int c0, int c1) {
    asm volatile("cp.async.bulk.prefetch.tensor.2d.L2.global.tile [%0, {%1, %2}];" ::"l"(m), "r"(c0), "r"(c1) : "memory");
}

__device__ __forceinline__ void cnt_wait(uint32_t addr, uint32_t need) {
    uint32_t v;
    do { asm volatile("ld.acquire.cta.shared.u32 %0, [%1];" : "=r"(v) : "r"(addr) : "memory"); } while (v < need);
}
__device__ __forceinline__ void dep_wait(uint32_t sb, uint32_t need) { cnt_wait(sb + DEP_CNT, need); }

__global__ void __launch_bounds__(384, 1)
fused_kernel(const __grid_constant__ Ptrs pt, const __grid_constant__ Maps tm) {
    extern __shared__ unsigned char smem_raw[];
    const uint32_t sb = (s2u(smem_raw) + 1023) & ~1023u;
    const int tid = threadIdx.x, lane = tid & 31;
    const int warp = __shfl_sync(0xffffffffu, tid >> 5, 0);
    const int rank = blockIdx.x & 1;
    const int cid = blockIdx.x >> 1;
    const int j = cid & 7;
    const int rb = (cid >> 3) * 2 + rank;
    const int npass = n_passes(j);
    const int n = j & 1;
    const int part = j >> 1;

    {
        const int l8 = lane & 7, sub = lane >> 3;
        uint4 v[3][7];
#pragma unroll
        for (int it = 0; it < 3; it++) {
            const int qd = warp + 12 * it;
            if (qd < 32) {
                const uint4* src = reinterpret_cast<const uint4*>(pt.x + (size_t)(rb * 128 + qd * 4 + sub) * D_) + l8;
#pragma unroll
                for (int i = 0; i < 7; i++) v[it][i] = __ldg(src + i * 8);
            }
        }
        if (tid == 256) {
            TL(0, 0);
            for (int i = 0; i < S1_STAGES; i++) { mbar_init(sb + BAR_F1 + 8 * i, 1); mbar_init(sb + BAR_E1 + 8 * i, 8); }
            for (int i = 0; i < Y_STAGES; i++) { mbar_init(sb + BAR_F2 + 8 * i, 1); mbar_init(sb + BAR_E2 + 8 * i, 16); }
            mbar_init(sb + BAR_S1DONE, 16);
            mbar_init(sb + BAR_SF, 4);
            asm volatile("st.shared.u32 [%0], %1;" ::"r"(sb + SE_CNT), "r"(0) : "memory");
            asm volatile("st.shared.u32 [%0], %1;" ::"r"(sb + DEP_CNT), "r"(0) : "memory");
            asm volatile("fence.mbarrier_init.release.cluster;" ::: "memory");
        }
        __syncwarp();
        asm volatile("barrier.cluster.arrive.relaxed.aligned;\nbarrier.cluster.wait.aligned;" ::: "memory");
        if (tid == 256) {
            const int slab = pass_slab(j, 0);
            for (int kb = 0; kb < S1_STAGES; kb++) {
                const uint32_t dst = sb + S1_B + kb * 16384 + rank * 8192;
                const uint32_t fb = sb + BAR_F1 + 8 * kb;
                mbar_expect(fb, 16384);
                if (slab >= 0) {
                    tma_load_mc(dst, rank ? &tm.wu : &tm.wg, fb, slab * 64, kb * 64);
                } else {
                    const int a = 2 * j + rank;
                    tma_load_mc(dst, a < 7 ? &tm.hre : &tm.him, fb, kb * 64, (a < 7 ? a : a - 7) * 64);
                }
            }
            const int b = blockIdx.x;
            l2_prefetch((const char*)pt.wg + b * 12544, 12544);
            l2_prefetch((const char*)pt.wu + b * 12544, 12544);
            l2_prefetch((const char*)pt.wd + b * 12544, 12544);
        }
        __syncwarp();
        if (tid == 0) TL(0, 1);
#pragma unroll
        for (int it = 0; it < 3; it++) {
            const int qd = warp + 12 * it;
            if (qd < 32) {
                const int row = qd * 4 + sub;
                float s0 = 0.f, s1 = 0.f;
#pragma unroll
                for (int i = 0; i < 7; i++) {
                    s0 += (bf_lo(v[it][i].x) + bf_hi(v[it][i].x)) + (bf_lo(v[it][i].y) + bf_hi(v[it][i].y));
                    s1 += (bf_lo(v[it][i].z) + bf_hi(v[it][i].z)) + (bf_lo(v[it][i].w) + bf_hi(v[it][i].w));
                }
                float s = s0 + s1;
                s += __shfl_xor_sync(0xffffffffu, s, 1);
                s += __shfl_xor_sync(0xffffffffu, s, 2);
                s += __shfl_xor_sync(0xffffffffu, s, 4);
                if (it == 0 && tid == 0) TL(0, 3);
                const float mean = s * (1.0f / D_);
                float q0 = 0.f, q1 = 0.f;
#pragma unroll
                for (int i = 0; i < 7; i++) {
                    const uint32_t w[4] = {v[it][i].x, v[it][i].y, v[it][i].z, v[it][i].w};
#pragma unroll
                    for (int c = 0; c < 4; c++) {
                        const float d0 = bf_lo(w[c]) - mean, d1 = bf_hi(w[c]) - mean;
                        q0 = fmaf(d0, d0, q0);
                        q1 = fmaf(d1, d1, q1);
                    }
                }
                float q = q0 + q1;
                q += __shfl_xor_sync(0xffffffffu, q, 1);
                q += __shfl_xor_sync(0xffffffffu, q, 2);
                q += __shfl_xor_sync(0xffffffffu, q, 4);
                const float var = rbf(q * (1.0f / D_));
                const float den = rbf(sqrtf(rbf(var + 1e-5f)));
                const float rinv = 1.0f / den;
                const float rhi = rbf(rinv);
                const uint32_t m2 = pack_bf16(mean, mean), rhi2 = pack_bf16(rhi, rhi), rlo2 = pack_bf16(rinv - rhi, rinv - rhi);
                const uint32_t dst = sb + S1_XN + row * 128 + ((l8 ^ (row & 7)) << 4);
#pragma unroll
                for (int i = 0; i < 7; i++) {
                    const uint32_t w[4] = {v[it][i].x, v[it][i].y, v[it][i].z, v[it][i].w};
                    uint32_t o[4];
#pragma unroll
                    for (int c = 0; c < 4; c++) {
                        const uint32_t xc = hsub2(w[c], m2);
                        o[c] = hfma2(xc, rhi2, hmul2(xc, rlo2));
                    }
                    asm volatile("st.shared.v4.b32 [%0], {%1, %2, %3, %4};" ::"r"(dst + i * 16384), "r"(o[0]), "r"(o[1]), "r"(o[2]), "r"(o[3]) : "memory");
                }
            }
        }
        fence_async();
        __syncthreads();
        if (tid == 0) TL(0, 2);
    }

    if (warp >= 8) {
        asm volatile("setmaxnreg.dec.sync.aligned.u32 40;");
        if (warp == 8) {
            if (lane == 0) {
                int st = 0;
                uint32_t ph = 0;
                for (int p = 0; p < npass; p++) {
                    const int slab = pass_slab(j, p);
                    for (int kb = p ? 0 : S1_STAGES; kb < 7; kb++) {
                        mbar_wait(sb + BAR_E1 + 8 * st, ph);
                        const uint32_t dst = sb + S1_B + st * 16384 + rank * 8192;
                        const uint32_t fb = sb + BAR_F1 + 8 * st;
                        mbar_expect(fb, 16384);
                        if (slab >= 0) {
                            tma_load_mc(dst, rank ? &tm.wu : &tm.wg, fb, slab * 64, kb * 64);
                        } else {
                            const int a = 2 * j + rank;
                            tma_load_mc(dst, a < 7 ? &tm.hre : &tm.him, fb, kb * 64, (a < 7 ? a : a - 7) * 64);
                        }
                        if (++st == S1_STAGES) { st = 0; ph ^= 1; }
                    }
                }
                if (part < 3) {
                    mbar_wait(sb + BAR_S1DONE, 0);
                    TL(0, 24);
                    st = 0; ph = 1;
                    if (part < 2) {
                        const CUtensorMap* ma = part ? &tm.sim : &tm.sre;
                        for (int g = 0; g < 32; g++) {
                            mbar_wait(sb + BAR_E2 + 8 * st, ph);
                            const uint32_t dst = sb + st * Y_STAGE;
                            const uint32_t fb = sb + BAR_F2 + 8 * st;
                            mbar_expect(fb, Y_STAGE);
                            tma_load(dst, ma, fb, g * 64, rb * 128);
                            dep_wait(sb, (g >> 1) + 1);
                            tma_load_mc(dst + 16384 + rank * 14336, &tm.abT, fb, g * 64, part * 448 + n * 224 + rank * 112);
                            if (++st == Y_STAGES) { st = 0; ph ^= 1; }
                        }
                    } else {
                        for (int g = 0; g < 28; g++) {
                            mbar_wait(sb + BAR_E2 + 8 * st, ph);
                            const uint32_t dst = sb + st * F_STAGE;
                            const uint32_t fb = sb + BAR_F2 + 8 * st;
                            mbar_expect(fb, F_STAGE);
                            tma_load_mc(dst + 16384 + (2 * rank) * 8192, &tm.wd, fb, n * 224 + (2 * rank) * 64, g * 64);
                            tma_load_mc(dst + 16384 + (2 * rank + 1) * 8192, &tm.wd, fb, n * 224 + (2 * rank + 1) * 64, g * 64);
                            dep_wait(sb, g + 1);
                            tma_load(dst, &tm.h, fb, g * 64, rb * 128);
                            if (++st == F_STAGES) { st = 0; ph ^= 1; }
                        }
                    }
                }
            }
        } else if (warp == 9) {
            if (part < 3) {
                if (part < 2 && lane < 16) {
                    tma_prefetch(part ? &tm.sim : &tm.sre, (2 * lane + n) * 64, rb * 128);
                }
                const int ndep = part < 2 ? 16 : 29;
                const unsigned int epoch = *(volatile unsigned int*)&g_fl.done / gridDim.x + 1;
                const unsigned int* f = part < 2 ? &g_fl.ab[lane & 15] : (lane < 28 ? &g_fl.h[rb * 28 + lane] : &g_fl.y[rb * 2 + n]);
                const unsigned int target = (part < 2 ? 7 : (lane < 28 ? 1 : 16)) * epoch;
                bool ok = lane >= ndep;
                int published = 0;
                for (int spins = 0; published < ndep && spins < (1 << 22); spins++) {
                    if (!ok) {
                        unsigned int v;
                        asm volatile("ld.acquire.gpu.global.u32 %0, [%1];" : "=r"(v) : "l"(f) : "memory");
                        ok = (int)(v - target) >= 0;
                    }
                    const unsigned int m = __ballot_sync(0xffffffffu, ok);
                    const int cnt = min(__ffs(~m) - 1, ndep);
                    if (m == 0xffffffffu || cnt > published) {
                        published = (m == 0xffffffffu) ? ndep : cnt;
                        fence_async_all();
                        __syncwarp();
                        if (lane == 0) asm volatile("st.release.cta.shared.u32 [%0], %1;" ::"r"(sb + DEP_CNT), "r"(published) : "memory");
                    }
                }
                if (published < ndep && lane == 0)
                    asm volatile("st.release.cta.shared.u32 [%0], %1;" ::"r"(sb + DEP_CNT), "r"(ndep) : "memory");
            }
        } else if (warp == 10) {
            if (lane == 0) {
                uint32_t u = 0;
                for (int p = 0; p < npass; p++) {
                    const int slab = pass_slab(j, p);
                    for (int hf = 0; hf < (slab < 0 ? 2 : 1); hf++) {
                        mbar_wait(sb + BAR_SF, u & 1);
                        u++;
                        if (slab >= 0) tma_store(&tm.h, sb + STG, slab * 64, rb * 128);
                        else tma_store(&tm.abT_st, sb + STG, rb * 128 + hf * 64, j * 128);
                        bulk_commit();
                        bulk_wait_read0();
                        asm volatile("st.release.cta.shared.u32 [%0], %1;" ::"r"(sb + SE_CNT), "r"(u) : "memory");
                    }
                    bulk_wait0();
                    fence_async_all();
                    flag_add(slab >= 0 ? &g_fl.h[rb * 28 + slab] : &g_fl.ab[rb]);
                }
            }
        }
        __syncwarp();
    } else {
        asm volatile("setmaxnreg.inc.sync.aligned.u32 232;");
        const int wg = warp >> 2, wl = warp & 3, wtid = tid & 127;
        const int qd = lane & 3;
        {
            float acc[2][64];
            for (int p = wg; p < npass; p += 2) {
                const int slab = pass_slab(j, p);
                if (p > 0) bar_sync(4 + (p & 1), 256);
                const int handoff = (p + 1 < npass) ? 4 + ((p + 1) & 1) : 0;
                if (slab >= 0) s1_mainloop<1>(acc, sb, p, lane, handoff);
                else s1_mainloop<0>(acc, sb, p, lane, handoff);
                if (p + 2 >= npass && part < 3 && lane == 0) mbar_arrive_both(sb + BAR_S1DONE);
                if (wtid == 0 && p < 4) TL(0, 4 + p);

                const int u0 = (j < 7 && p > 0) ? p + 1 : p;
                const uint32_t srow = sb + STG + (wl * 16 + (lane & 7) + ((lane >> 3) & 1) * 8) * 128;
                if (slab >= 0) {
                    uint32_t hv[2][16];
#pragma unroll
                    for (int mh = 0; mh < 2; mh++) {
#pragma unroll
                        for (int i = 0; i < 16; i++) {
                            const uint32_t g2 = pack_bf16(acc[mh][2 * i], acc[mh][2 * i + 1]);
                            const uint32_t u2 = pack_bf16(acc[mh][32 + 2 * i], acc[mh][32 + 2 * i + 1]);
                            const uint32_t a2 = pack_bf16(gelu_tanh(bf_lo(g2)), gelu_tanh(bf_hi(g2)));
                            hv[mh][i] = hmul2(a2, u2);
                        }
                    }
                    cnt_wait(sb + SE_CNT, u0);
#pragma unroll
                    for (int mh = 0; mh < 2; mh++) {
#pragma unroll
                        for (int jj = 0; jj < 8; jj += 2)
                            stmat4(srow + mh * 8192 + (((jj + (lane >> 4)) ^ (lane & 7)) << 4),
                                   hv[mh][2 * jj], hv[mh][2 * jj + 1], hv[mh][2 * jj + 2], hv[mh][2 * jj + 3]);
                    }
                    fence_async();
                    __syncwarp();
                    if (lane == 0) mbar_arrive(sb + BAR_SF);
                } else {
#pragma unroll
                    for (int hf = 0; hf < 2; hf++) {
                        cnt_wait(sb + SE_CNT, hf);
#pragma unroll
                        for (int mh = 0; mh < 2; mh++) {
#pragma unroll
                            for (int jj = 0; jj < 8; jj += 2) {
                                const int o = hf * 32 + jj * 4;
                                stmat4(srow + mh * 8192 + (((jj + (lane >> 4)) ^ (lane & 7)) << 4),
                                       pack_bf16(acc[mh][o], acc[mh][o + 1]), pack_bf16(acc[mh][o + 2], acc[mh][o + 3]),
                                       pack_bf16(acc[mh][o + 4], acc[mh][o + 5]), pack_bf16(acc[mh][o + 6], acc[mh][o + 7]));
                            }
                        }
                        fence_async();
                        __syncwarp();
                        if (lane == 0) mbar_arrive(sb + BAR_SF);
                    }
                }
                if (wtid == 0 && p < 4) TL(0, 10 + p);
            }
        }
        if (wtid == 0) TL(0, 20 + wg);
        if (part < 3) {
            {
                float acc[112];
                const size_t base = (size_t)(rb * 128 + wg * 64 + wl * 16 + (lane >> 2)) * D_ + n * 224 + qd * 8;
                if (part < 2) {
                    s2_mainloop<0>(acc, sb, wg, lane);
                    if (tid == 0) TL(0, 25);
                    uint4* dst = g_y + (size_t)((part * 32 + rb * 2 + n) * 14) * 256 + tid;
#pragma unroll
                    for (int i = 0; i < 14; i++)
                        __stcg(dst + i * 256, make_uint4(pack_bf16(acc[8 * i], acc[8 * i + 1]), pack_bf16(acc[8 * i + 2], acc[8 * i + 3]),
                                                         pack_bf16(acc[8 * i + 4], acc[8 * i + 5]), pack_bf16(acc[8 * i + 6], acc[8 * i + 7])));
                    __threadfence();
                    __syncwarp();
                    if (lane == 0) flag_add(&g_fl.y[rb * 2 + n]);
                } else {
                    uint4 xv[14];
#pragma unroll
                    for (int i = 0; i < 14; i++)
                        xv[i] = __ldg(reinterpret_cast<const uint4*>(pt.x + base + (i / 7) * 8 * D_ + (i % 7) * 32));
                    s2_mainloop<1>(acc, sb, wg, lane);
                    if (tid == 0) TL(0, 25);
                    dep_wait(sb, 29);
                    if (tid == 0) TL(0, 26);
                    const uint4* ysrc = g_y + (size_t)((rb * 2 + n) * 14) * 256 + tid;
                    uint4 yr[14], yi[14];
#pragma unroll
                    for (int i = 0; i < 14; i++) yr[i] = __ldcg(ysrc + i * 256);
                    uint32_t sg[56];
#pragma unroll
                    for (int i = 0; i < 56; i++) {
                        const uint32_t f2 = pack_bf16(acc[2 * i], acc[2 * i + 1]);
                        sg[i] = pack_bf16(silu(bf_lo(f2)), silu(bf_hi(f2)));
                    }
#pragma unroll
                    for (int i = 0; i < 14; i++) yi[i] = __ldcg(ysrc + (32 * 14 + i) * 256);
#pragma unroll
                    for (int i = 0; i < 14; i++) {
                        sg[4 * i + 0] = hmul2(hsub2(yr[i].x, yi[i].x), sg[4 * i + 0]);
                        sg[4 * i + 1] = hmul2(hsub2(yr[i].y, yi[i].y), sg[4 * i + 1]);
                        sg[4 * i + 2] = hmul2(hsub2(yr[i].z, yi[i].z), sg[4 * i + 2]);
                        sg[4 * i + 3] = hmul2(hsub2(yr[i].w, yi[i].w), sg[4 * i + 3]);
                    }
#pragma unroll
                    for (int hh = 0; hh < 2; hh++) {
#pragma unroll
                        for (int g4 = 0; g4 < 7; g4++) {
                            uint32_t r[4];
#pragma unroll
                            for (int t = 0; t < 4; t++) r[t] = sg[(g4 * 4 + t) * 2 + hh];
                            quad_transpose(r, qd);
                            const uint4 xx = xv[hh * 7 + g4];
                            *reinterpret_cast<uint4*>(pt.out + base + hh * 8 * D_ + g4 * 32) =
                                make_uint4(hadd2(xx.x, r[0]), hadd2(xx.y, r[1]), hadd2(xx.z, r[2]), hadd2(xx.w, r[3]));
                        }
                    }
                }
            }
        }
    }
    if (tid == 0) TL(0, 29);
    __syncthreads();
    if (tid == 0) {
        TL(0, 30);
        atomicAdd(&g_fl.done, 1u);
    }
}

typedef CUresult (*EncFn)(CUtensorMap*, CUtensorMapDataType, cuuint32_t, void*, const cuuint64_t*, const cuuint64_t*,
                          const cuuint32_t*, const cuuint32_t*, CUtensorMapInterleave, CUtensorMapSwizzle,
                          CUtensorMapL2promotion, CUtensorMapFloatOOBfill);

void make_map(EncFn enc, CUtensorMap* m, const void* ptr, int rows, int cols, int box_rows, int box_cols, int pitch = 0) {
    const bool swz = true;
    cuuint64_t gd[2] = {(cuuint64_t)cols, (cuuint64_t)rows};
    cuuint64_t gs[1] = {(cuuint64_t)(pitch ? pitch : cols) * 2};
    cuuint32_t bx[2] = {(cuuint32_t)box_cols, (cuuint32_t)box_rows};
    cuuint32_t es[2] = {1, 1};
    enc(m, CU_TENSOR_MAP_DATA_TYPE_BFLOAT16, 2, const_cast<void*>(ptr), gd, gs, bx, es, CU_TENSOR_MAP_INTERLEAVE_NONE,
        swz ? CU_TENSOR_MAP_SWIZZLE_128B : CU_TENSOR_MAP_SWIZZLE_NONE, CU_TENSOR_MAP_L2_PROMOTION_L2_128B,
        CU_TENSOR_MAP_FLOAT_OOB_FILL_NONE);
}

}

extern "C" void kernel_launch(void* const* d_in, const int* in_sizes, int n_in, void* d_out, int out_size) {
    Ptrs pt;
    pt.x = (const __nv_bfloat16*)d_in[0];
    pt.hre = (const __nv_bfloat16*)d_in[3];
    pt.him = (const __nv_bfloat16*)d_in[4];
    pt.wg = (const __nv_bfloat16*)d_in[6];
    pt.wu = (const __nv_bfloat16*)d_in[7];
    pt.wd = (const __nv_bfloat16*)d_in[8];
    pt.out = (__nv_bfloat16*)d_out;

    void* fn = nullptr;
    cudaDriverEntryPointQueryResult qr;
    cudaGetDriverEntryPoint("cuTensorMapEncodeTiled", &fn, cudaEnableDefault, &qr);
    EncFn enc = (EncFn)fn;
    void *p_abT, *p_h;
    cudaGetSymbolAddress(&p_abT, g_abT);
    cudaGetSymbolAddress(&p_h, g_h);

    Maps tm;
    make_map(enc, &tm.wg, d_in[6], D_, F_, 64, 64);
    make_map(enc, &tm.wu, d_in[7], D_, F_, 64, 64);
    make_map(enc, &tm.hre, d_in[3], D_, D_, 64, 64);
    make_map(enc, &tm.him, d_in[4], D_, D_, 64, 64);
    make_map(enc, &tm.h, p_h, S_, F_, 128, 64);
    make_map(enc, &tm.abT, p_abT, 896, S_, 112, 64, ABP);
    make_map(enc, &tm.abT_st, p_abT, 896, S_, 128, 64, ABP);
    make_map(enc, &tm.sre, d_in[1], S_, S_, 128, 64);
    make_map(enc, &tm.sim, d_in[2], S_, S_, 128, 64);
    make_map(enc, &tm.wd, d_in[8], F_, D_, 64, 64);

    cudaFuncSetAttribute(fused_kernel, cudaFuncAttributeMaxDynamicSharedMemorySize, SMEM_BYTES);

    cudaLaunchAttribute at[1];
    at[0].id = cudaLaunchAttributeClusterDimension;
    at[0].val.clusterDim.x = 2; at[0].val.clusterDim.y = 1; at[0].val.clusterDim.z = 1;
    cudaLaunchConfig_t cfg = {};
    cfg.gridDim = dim3(128); cfg.blockDim = dim3(384); cfg.stream = cudaStreamPerThread;
    cfg.attrs = at; cfg.numAttrs = 1;
    cfg.dynamicSmemBytes = SMEM_BYTES;
    cudaLaunchKernelEx(&cfg, fused_kernel, pt, tm);
}
```

```cpp
#include <cuda_runtime.h>
#include <cuda_bf16.h>
#include <cuda.h>
#include <stdint.h>

namespace {

constexpr int S_ = 2048, D_ = 448, F_ = 1792;

constexpr int ABP = 2048 + 64;
__device__ __align__(1024) __nv_bfloat16 g_abT[896 * ABP];
__device__ __align__(1024) __nv_bfloat16 g_h[2048 * 1792];
__device__ __align__(1024) uint4 g_y[2 * 32 * 14 * 256];
struct Flags {
    unsigned int ab[16];
    unsigned int h[16 * 28];
    unsigned int y[32];
    unsigned int done;
};
__device__ Flags g_fl;

#define TL(k, i) do {} while (0)
__device__ __forceinline__ uint32_t s2u(const void* p) { return (uint32_t)__cvta_generic_to_shared(p); }
__device__ __forceinline__ void mbar_init(uint32_t b, int c) {
    asm volatile("mbarrier.init.shared::cta.b64 [%0], %1;" ::"r"(b), "r"(c));
}
__device__ __forceinline__ void mbar_expect(uint32_t b, uint32_t bytes) {
    asm volatile("mbarrier.arrive.expect_tx.shared::cta.b64 _, [%0], %1;" ::"r"(b), "r"(bytes) : "memory");
}
__device__ __forceinline__ void mbar_wait(uint32_t b, uint32_t ph) {
    uint32_t ok;
    do {
        asm volatile("{\n.reg .pred p;\nmbarrier.try_wait.parity.shared::cta.b64 p, [%1], %2;\nselp.u32 %0, 1, 0, p;\n}"
                     : "=r"(ok) : "r"(b), "r"(ph) : "memory");
    } while (!ok);
}
__device__ __forceinline__ void mbar_arrive_both(uint32_t b) {
    asm volatile("{\n.reg .b32 r0, r1;\n"
                 "mapa.shared::cluster.u32 r0, %0, 0;\n"
                 "mapa.shared::cluster.u32 r1, %0, 1;\n"
                 "mbarrier.arrive.shared::cluster.b64 _, [r0];\n"
                 "mbarrier.arrive.shared::cluster.b64 _, [r1];\n}"
                 ::"r"(b) : "memory");
}
__device__ __forceinline__ void tma_load(uint32_t dst, const CUtensorMap* m, uint32_t bar, int c0, int c1) {
    asm volatile("cp.async.bulk.tensor.2d.shared::cluster.global.mbarrier::complete_tx::bytes [%0], [%1, {%3, %4}], [%2];"
                 ::"r"(dst), "l"(m), "r"(bar), "r"(c0), "r"(c1) : "memory");
}
__device__ __forceinline__ void tma_load_mc(uint32_t dst, const CUtensorMap* m, uint32_t bar, int c0, int c1) {
    asm volatile("cp.async.bulk.tensor.2d.shared::cluster.global.mbarrier::complete_tx::bytes.multicast::cluster [%0], [%1, {%3, %4}], [%2], %5;"
                 ::"r"(dst), "l"(m), "r"(bar), "r"(c0), "r"(c1), "h"((uint16_t)3) : "memory");
}
__device__ __forceinline__ void tma_store(const CUtensorMap* m, uint32_t src, int c0, int c1) {
    asm volatile("cp.async.bulk.tensor.2d.global.shared::cta.bulk_group [%0, {%2, %3}], [%1];"
                 ::"l"(m), "r"(src), "r"(c0), "r"(c1) : "memory");
}
__device__ __forceinline__ void bulk_commit() { asm volatile("cp.async.bulk.commit_group;" ::: "memory"); }
__device__ __forceinline__ void bulk_wait_read0() { asm volatile("cp.async.bulk.wait_group.read 0;" ::: "memory"); }
__device__ __forceinline__ void bulk_wait0() { asm volatile("cp.async.bulk.wait_group 0;" ::: "memory"); }
__device__ __forceinline__ void fence_async() { asm volatile("fence.proxy.async.shared::cta;" ::: "memory"); }
__device__ __forceinline__ void fence_async_all() { asm volatile("fence.proxy.async;" ::: "memory"); }
__device__ __forceinline__ void cluster_sync() {
    asm volatile("barrier.cluster.arrive.release.aligned;\nbarrier.cluster.wait.acquire.aligned;" ::: "memory");
}
__device__ __forceinline__ void bar_sync(int id, int n) { asm volatile("bar.sync %0, %1;" ::"r"(id), "r"(n) : "memory"); }
__device__ __forceinline__ void wg_arrive() { asm volatile("wgmma.fence.sync.aligned;" ::: "memory"); }
__device__ __forceinline__ void wg_commit() { asm volatile("wgmma.commit_group.sync.aligned;" ::: "memory"); }
template <int N> __device__ __forceinline__ void wg_wait() { asm volatile("wgmma.wait_group.sync.aligned %0;" ::"n"(N) : "memory"); }
__device__ __forceinline__ void stmat4(uint32_t a, uint32_t r0, uint32_t r1, uint32_t r2, uint32_t r3) {
    asm volatile("stmatrix.sync.aligned.m8n8.x4.shared.b16 [%0], {%1, %2, %3, %4};" ::"r"(a), "r"(r0), "r"(r1), "r"(r2), "r"(r3) : "memory");
}
__device__ __forceinline__ void stmat4t(uint32_t a, uint32_t r0, uint32_t r1, uint32_t r2, uint32_t r3) {
    asm volatile("stmatrix.sync.aligned.m8n8.x4.trans.shared.b16 [%0], {%1, %2, %3, %4};" ::"r"(a), "r"(r0), "r"(r1), "r"(r2), "r"(r3) : "memory");
}
__device__ __forceinline__ void ldmat4(uint32_t a, uint32_t (&r)[4]) {
    asm volatile("ldmatrix.sync.aligned.m8n8.x4.shared.b16 {%0, %1, %2, %3}, [%4];"
                 : "=r"(r[0]), "=r"(r[1]), "=r"(r[2]), "=r"(r[3]) : "r"(a) : "memory");
}
__device__ __forceinline__ void flag_add(unsigned int* f) {
    asm volatile("red.release.gpu.global.add.u32 [%0], 1;" ::"l"(f) : "memory");
}
__device__ __forceinline__ void flag_wait(const unsigned int* f, unsigned int target) {
    unsigned int v;
    int spins = 0;
    while (true) {
        asm volatile("ld.acquire.gpu.global.u32 %0, [%1];" : "=r"(v) : "l"(f) : "memory");
        if ((int)(v - target) >= 0 || ++spins > (1 << 22)) break;
    }
}
__device__ __forceinline__ void quad_transpose(uint32_t (&r)[4], int q) {
    const bool o1 = q & 1, o2 = q & 2;
    uint32_t a = o1 ? r[0] : r[1], b = o1 ? r[2] : r[3];
    a = __shfl_xor_sync(0xffffffffu, a, 1);
    b = __shfl_xor_sync(0xffffffffu, b, 1);
    if (o1) { r[0] = a; r[2] = b; } else { r[1] = a; r[3] = b; }
    a = o2 ? r[0] : r[2]; b = o2 ? r[1] : r[3];
    a = __shfl_xor_sync(0xffffffffu, a, 2);
    b = __shfl_xor_sync(0xffffffffu, b, 2);
    if (o2) { r[0] = a; r[1] = b; } else { r[2] = a; r[3] = b; }
}
__device__ __forceinline__ uint32_t movmat_t(uint32_t v) {
    uint32_t r;
    asm volatile("movmatrix.sync.aligned.m8n8.trans.b16 %0, %1;" : "=r"(r) : "r"(v));
    return r;
}
__device__ __forceinline__ uint64_t mkdesc(uint32_t addr, uint32_t lbo, uint32_t sbo) {
    return (uint64_t)((addr & 0x3FFFF) >> 4) | ((uint64_t)(lbo >> 4) << 16) | ((uint64_t)(sbo >> 4) << 32) | (1ull << 62);
}
__device__ __forceinline__ uint32_t pack_bf16(float lo, float hi) {
    uint32_t r;
    asm("cvt.rn.bf16x2.f32 %0, %1, %2;" : "=r"(r) : "f"(hi), "f"(lo));
    return r;
}
__device__ __forceinline__ uint32_t hsub2(uint32_t a, uint32_t b) { uint32_t r; asm("sub.rn.bf16x2 %0, %1, %2;" : "=r"(r) : "r"(a), "r"(b)); return r; }
__device__ __forceinline__ uint32_t hadd2(uint32_t a, uint32_t b) { uint32_t r; asm("add.rn.bf16x2 %0, %1, %2;" : "=r"(r) : "r"(a), "r"(b)); return r; }
__device__ __forceinline__ uint32_t hmul2(uint32_t a, uint32_t b) { uint32_t r; asm("mul.rn.bf16x2 %0, %1, %2;" : "=r"(r) : "r"(a), "r"(b)); return r; }
__device__ __forceinline__ uint32_t hfma2(uint32_t a, uint32_t b, uint32_t c) { uint32_t r; asm("fma.rn.bf16x2 %0, %1, %2, %3;" : "=r"(r) : "r"(a), "r"(b), "r"(c)); return r; }
__device__ __forceinline__ float bf_lo(uint32_t u) { return __uint_as_float(u << 16); }
__device__ __forceinline__ float bf_hi(uint32_t u) { return __uint_as_float(u & 0xffff0000u); }
__device__ __forceinline__ float rbf(float v) { return __bfloat162float(__float2bfloat16_rn(v)); }
__device__ __forceinline__ float tanh_fast(float x) { float r; asm("tanh.approx.f32 %0, %1;" : "=f"(r) : "f"(x)); return r; }
__device__ __forceinline__ float gelu_tanh(float x) {
    float u = x * fmaf(x * x, 0.0356774081f, 0.7978845608f);
    float hx = 0.5f * x;
    return fmaf(hx, tanh_fast(u), hx);
}
__device__ __forceinline__ float silu(float f) { const float hf = 0.5f * f; return fmaf(hf, tanh_fast(hf), hf); }

template <int TB>
__device__ __forceinline__ void wgmma_n128(float (&d)[64], uint64_t da, uint64_t db, int scaleD) {
    asm volatile("{\n.reg .pred p;\nsetp.ne.b32 p, %66, 0;\n"
        "wgmma.mma_async.sync.aligned.m64n128k16.f32.bf16.bf16 {%0, %1, %2, %3, %4, %5, %6, %7, %8, %9, %10, %11, %12, %13, %14, %15, %16, %17, %18, %19, %20, %21, %22, %23, %24, %25, %26, %27, %28, %29, %30, %31, %32, %33, %34, %35, %36, %37, %38, %39, %40, %41, %42, %43, %44, %45, %46, %47, %48, %49, %50, %51, %52, %53, %54, %55, %56, %57, %58, %59, %60, %61, %62, %63}, %64, %65, p, 1, 1, 0, %67;\n}\n"
        : "+f"(d[0]), "+f"(d[1]), "+f"(d[2]), "+f"(d[3]), "+f"(d[4]), "+f"(d[5]), "+f"(d[6]), "+f"(d[7]), "+f"(d[8]), "+f"(d[9]), "+f"(d[10]), "+f"(d[11]), "+f"(d[12]), "+f"(d[13]), "+f"(d[14]), "+f"(d[15]), "+f"(d[16]), "+f"(d[17]), "+f"(d[18]), "+f"(d[19]), "+f"(d[20]), "+f"(d[21]), "+f"(d[22]), "+f"(d[23]), "+f"(d[24]), "+f"(d[25]), "+f"(d[26]), "+f"(d[27]), "+f"(d[28]), "+f"(d[29]), "+f"(d[30]), "+f"(d[31]), "+f"(d[32]), "+f"(d[33]), "+f"(d[34]), "+f"(d[35]), "+f"(d[36]), "+f"(d[37]), "+f"(d[38]), "+f"(d[39]), "+f"(d[40]), "+f"(d[41]), "+f"(d[42]), "+f"(d[43]), "+f"(d[44]), "+f"(d[45]), "+f"(d[46]), "+f"(d[47]), "+f"(d[48]), "+f"(d[49]), "+f"(d[50]), "+f"(d[51]), "+f"(d[52]), "+f"(d[53]), "+f"(d[54]), "+f"(d[55]), "+f"(d[56]), "+f"(d[57]), "+f"(d[58]), "+f"(d[59]), "+f"(d[60]), "+f"(d[61]), "+f"(d[62]), "+f"(d[63])
        : "l"(da), "l"(db), "r"(scaleD), "n"(TB));
}
template <int TB>
__device__ __forceinline__ void wgmma_n224(float (&d)[112], uint64_t da, uint64_t db, int scaleD) {
    asm volatile("{\n.reg .pred p;\nsetp.ne.b32 p, %114, 0;\n"
        "wgmma.mma_async.sync.aligned.m64n224k16.f32.bf16.bf16 {%0, %1, %2, %3, %4, %5, %6, %7, %8, %9, %10, %11, %12, %13, %14, %15, %16, %17, %18, %19, %20, %21, %22, %23, %24, %25, %26, %27, %28, %29, %30, %31, %32, %33, %34, %35, %36, %37, %38, %39, %40, %41, %42, %43, %44, %45, %46, %47, %48, %49, %50, %51, %52, %53, %54, %55, %56, %57, %58, %59, %60, %61, %62, %63, %64, %65, %66, %67, %68, %69, %70, %71, %72, %73, %74, %75, %76, %77, %78, %79, %80, %81, %82, %83, %84, %85, %86, %87, %88, %89, %90, %91, %92, %93, %94, %95, %96, %97, %98, %99, %100, %101, %102, %103, %104, %105, %106, %107, %108, %109, %110, %111}, %112, %113, p, 1, 1, 0, %115;\n}\n"
        : "+f"(d[0]), "+f"(d[1]), "+f"(d[2]), "+f"(d[3]), "+f"(d[4]), "+f"(d[5]), "+f"(d[6]), "+f"(d[7]), "+f"(d[8]), "+f"(d[9]), "+f"(d[10]), "+f"(d[11]), "+f"(d[12]), "+f"(d[13]), "+f"(d[14]), "+f"(d[15]), "+f"(d[16]), "+f"(d[17]), "+f"(d[18]), "+f"(d[19]), "+f"(d[20]), "+f"(d[21]), "+f"(d[22]), "+f"(d[23]), "+f"(d[24]), "+f"(d[25]), "+f"(d[26]), "+f"(d[27]), "+f"(d[28]), "+f"(d[29]), "+f"(d[30]), "+f"(d[31]), "+f"(d[32]), "+f"(d[33]), "+f"(d[34]), "+f"(d[35]), "+f"(d[36]), "+f"(d[37]), "+f"(d[38]), "+f"(d[39]), "+f"(d[40]), "+f"(d[41]), "+f"(d[42]), "+f"(d[43]), "+f"(d[44]), "+f"(d[45]), "+f"(d[46]), "+f"(d[47]), "+f"(d[48]), "+f"(d[49]), "+f"(d[50]), "+f"(d[51]), "+f"(d[52]), "+f"(d[53]), "+f"(d[54]), "+f"(d[55]), "+f"(d[56]), "+f"(d[57]), "+f"(d[58]), "+f"(d[59]), "+f"(d[60]), "+f"(d[61]), "+f"(d[62]), "+f"(d[63]), "+f"(d[64]), "+f"(d[65]), "+f"(d[66]), "+f"(d[67]), "+f"(d[68]), "+f"(d[69]), "+f"(d[70]), "+f"(d[71]), "+f"(d[72]), "+f"(d[73]), "+f"(d[74]), "+f"(d[75]), "+f"(d[76]), "+f"(d[77]), "+f"(d[78]), "+f"(d[79]), "+f"(d[80]), "+f"(d[81]), "+f"(d[82]), "+f"(d[83]), "+f"(d[84]), "+f"(d[85]), "+f"(d[86]), "+f"(d[87]), "+f"(d[88]), "+f"(d[89]), "+f"(d[90]), "+f"(d[91]), "+f"(d[92]), "+f"(d[93]), "+f"(d[94]), "+f"(d[95]), "+f"(d[96]), "+f"(d[97]), "+f"(d[98]), "+f"(d[99]), "+f"(d[100]), "+f"(d[101]), "+f"(d[102]), "+f"(d[103]), "+f"(d[104]), "+f"(d[105]), "+f"(d[106]), "+f"(d[107]), "+f"(d[108]), "+f"(d[109]), "+f"(d[110]), "+f"(d[111])
        : "l"(da), "l"(db), "r"(scaleD), "n"(TB));
}

constexpr int S1_STAGES = 6;
constexpr int S1_XN = 0;
constexpr int S1_B = 7 * 16384;
constexpr int STG = S1_B + S1_STAGES * 16384;
constexpr int Y_STAGES = 4, Y_STAGE = 45056;
constexpr int F_STAGES = 4, F_STAGE = 49152;
constexpr int BAR = STG + 16384;
constexpr int BAR_F1 = BAR, BAR_E1 = BAR + 56, BAR_F2 = BAR + 112, BAR_E2 = BAR + 152, BAR_S1DONE = BAR + 192;
constexpr int BAR_SF = BAR + 208;
constexpr int SE_CNT = BAR + 216;
constexpr int DEP_CNT = BAR + 200;
constexpr int SMEM_BYTES = BAR + 256 + 1024;
constexpr int TPITCH = 464;

__device__ __forceinline__ int n_passes(int j) { return j < 4 ? 2 : (j < 6 ? 4 : 10); }
__device__ __forceinline__ int pass_slab(int j, int p) {
    if (p == 0) return j < 7 ? -1 : 0;
    if (p == 1) return 1 + j;
    if (p < 4) return 4 * p - 3 + j;
    if (p == 9) return 27;
    return 17 + 2 * (p - 4) + (j - 6);
}

template <int TB>
__device__ __forceinline__ void s1_mainloop(float (&acc)[2][64], uint32_t sb, int p, int lane, int handoff, int half = 0) {
    int st = (p * 7) % S1_STAGES;
    uint32_t ph = ((p * 7) / S1_STAGES) & 1;
    int prev = 0;
    uint64_t dx = mkdesc(sb + S1_XN + half * 8192, 16, 1024);
    const uint64_t dw0 = TB ? mkdesc(sb + S1_B, 8192, 1024) : mkdesc(sb + S1_B, 16, 1024);
    const int nrel = lane == 0 ? (handoff ? 7 : 7 - S1_STAGES) : 0;
#pragma unroll 1
    for (int kb = 0; kb < 7; kb++) {
        mbar_wait(sb + BAR_F1 + 8 * st, ph);
        if (kb == 6 && handoff) asm volatile("bar.arrive %0, 256;" ::"r"(handoff) : "memory");
        const uint64_t dw = dw0 + st * 1024;
        wg_arrive();
#pragma unroll
        for (int s = 0; s < 4; s++) {
            if (TB == 2) {
                wgmma_n128<1>(acc[0], dx + s * 2, dw + s * 128, kb | s);
            } else if (TB) {
                wgmma_n128<1>(acc[0], dx + s * 2, dw + s * 128, kb | s);
                wgmma_n128<1>(acc[1], dx + 512 + s * 2, dw + s * 128, kb | s);
            } else {
                wgmma_n128<0>(acc[0], dw + s * 2, dx + s * 2, kb | s);
                wgmma_n128<0>(acc[1], dw + 512 + s * 2, dx + s * 2, kb | s);
            }
        }
        wg_commit();
        wg_wait<1>();
        if (kb > 0 && kb <= nrel) mbar_arrive_both(sb + BAR_E1 + 8 * prev);
        prev = st;
        dx += 1024;
        if (++st == S1_STAGES) { st = 0; ph ^= 1; }
    }
    wg_wait<0>();
    if (nrel == 7) mbar_arrive_both(sb + BAR_E1 + 8 * prev);
}

template <int TB>
__device__ __forceinline__ void s2_mainloop(float (&acc)[112], uint32_t sb, int wg, int lane) {
    constexpr int NST = TB ? F_STAGES : Y_STAGES, SSZ = TB ? F_STAGE : Y_STAGE, NKB = TB ? 28 : 32;
    int st = 0;
    uint32_t ph = 0;
    int prev = 0;
    const uint64_t da0 = mkdesc(sb + wg * 8192, 16, 1024);
    const uint64_t db0 = TB ? mkdesc(sb + 16384, 8192, 1024) : mkdesc(sb + 16384, 16, 1024);
#pragma unroll 1
    for (int i = 0; i < NKB; i++) {
        mbar_wait(sb + BAR_F2 + 8 * st, ph);
        const uint64_t da = da0 + st * (SSZ / 16), db = db0 + st * (SSZ / 16);
        wg_arrive();
#pragma unroll
        for (int s = 0; s < 4; s++) wgmma_n224<TB>(acc, da + s * 2, db + s * (TB ? 128 : 2), i | s);
        wg_commit();
        wg_wait<1>();
        if (i > 0 && i <= NKB - NST && lane == 0) mbar_arrive_both(sb + BAR_E2 + 8 * prev);
        prev = st;
        if (++st == NST) { st = 0; ph ^= 1; }
    }
    wg_wait<0>();
}

struct Maps {
    CUtensorMap wg, wu, hre, him, h, h64, abT, abT_st, sre, sim, wd;
};
struct Ptrs {
    const __nv_bfloat16 *x, *hre, *him, *wg, *wu, *wd;
    __nv_bfloat16* out;
};
__device__ __forceinline__ void mbar_arrive(uint32_t b) {
    asm volatile("mbarrier.arrive.shared::cta.b64 _, [%0];" ::"r"(b) : "memory");
}
__device__ __forceinline__ void l2_prefetch(const void* p, uint32_t bytes) {
    asm volatile("cp.async.bulk.prefetch.L2.global [%0], %1;" ::"l"(p), "r"(bytes) : "memory");
}
__device__ __forceinline__ void tma_prefetch(const CUtensorMap* m, int c0, int c1) {
    asm volatile("cp.async.bulk.prefetch.tensor.2d.L2.global.tile [%0, {%1, %2}];" ::"l"(m), "r"(c0), "r"(c1) : "memory");
}

__device__ __forceinline__ void cnt_wait(uint32_t addr, uint32_t need) {
    uint32_t v;
    do { asm volatile("ld.acquire.cta.shared.u32 %0, [%1];" : "=r"(v) : "r"(addr) : "memory"); } while (v < need);
}
__device__ __forceinline__ void dep_wait(uint32_t sb, uint32_t need) { cnt_wait(sb + DEP_CNT, need); }

__global__ void __launch_bounds__(384, 1)
fused_kernel(const __grid_constant__ Ptrs pt, const __grid_constant__ Maps tm) {
    extern __shared__ unsigned char smem_raw[];
    const uint32_t sb = (s2u(smem_raw) + 1023) & ~1023u;
    const int tid = threadIdx.x, lane = tid & 31;
    const int warp = __shfl_sync(0xffffffffu, tid >> 5, 0);
    const int rank = blockIdx.x & 1;
    const int cid = blockIdx.x >> 1;
    const int j = cid & 7;
    const int rb = (cid >> 3) * 2 + rank;
    const int npass = n_passes(j);
    const int n = j & 1;
    const int part = j >> 1;

    {
        const int l8 = lane & 7, sub = lane >> 3;
        uint4 v[3][7];
#pragma unroll
        for (int it = 0; it < 3; it++) {
            const int qd = warp + 12 * it;
            if (qd < 32) {
                const uint4* src = reinterpret_cast<const uint4*>(pt.x + (size_t)(rb * 128 + qd * 4 + sub) * D_) + l8;
#pragma unroll
                for (int i = 0; i < 7; i++) v[it][i] = __ldg(src + i * 8);
            }
        }
        if (tid == 256) {
            TL(0, 0);
            for (int i = 0; i < S1_STAGES; i++) { mbar_init(sb + BAR_F1 + 8 * i, 1); mbar_init(sb + BAR_E1 + 8 * i, 8); }
            for (int i = 0; i < Y_STAGES; i++) { mbar_init(sb + BAR_F2 + 8 * i, 1); mbar_init(sb + BAR_E2 + 8 * i, 16); }
            mbar_init(sb + BAR_S1DONE, 16);
            mbar_init(sb + BAR_SF, 4);
            asm volatile("st.shared.u32 [%0], %1;" ::"r"(sb + SE_CNT), "r"(0) : "memory");
            asm volatile("st.shared.u32 [%0], %1;" ::"r"(sb + DEP_CNT), "r"(0) : "memory");
            asm volatile("fence.mbarrier_init.release.cluster;" ::: "memory");
        }
        __syncwarp();
        asm volatile("barrier.cluster.arrive.relaxed.aligned;\nbarrier.cluster.wait.aligned;" ::: "memory");
        if (tid == 256) {
            const int slab = pass_slab(j, 0);
            for (int kb = 0; kb < S1_STAGES; kb++) {
                const uint32_t dst = sb + S1_B + kb * 16384 + rank * 8192;
                const uint32_t fb = sb + BAR_F1 + 8 * kb;
                mbar_expect(fb, 16384);
                if (slab >= 0) {
                    tma_load_mc(dst, rank ? &tm.wu : &tm.wg, fb, slab * 64, kb * 64);
                } else {
                    const int a = 2 * j + rank;
                    tma_load_mc(dst, a < 7 ? &tm.hre : &tm.him, fb, kb * 64, (a < 7 ? a : a - 7) * 64);
                }
            }
            const int b = blockIdx.x;
            l2_prefetch((const char*)pt.hre + b * 3136, 3136);
            l2_prefetch((const char*)pt.him + b * 3136, 3136);
            l2_prefetch((const char*)pt.wg + b * 12544, 12544);
            l2_prefetch((const char*)pt.wu + b * 12544, 12544);
            l2_prefetch((const char*)pt.wd + b * 12544, 12544);
        }
        __syncwarp();
        if (tid == 0) TL(0, 1);
#pragma unroll
        for (int it = 0; it < 3; it++) {
            const int qd = warp + 12 * it;
            if (qd < 32) {
                const int row = qd * 4 + sub;
                float s0 = 0.f, s1 = 0.f;
#pragma unroll
                for (int i = 0; i < 7; i++) {
                    s0 += (bf_lo(v[it][i].x) + bf_hi(v[it][i].x)) + (bf_lo(v[it][i].y) + bf_hi(v[it][i].y));
                    s1 += (bf_lo(v[it][i].z) + bf_hi(v[it][i].z)) + (bf_lo(v[it][i].w) + bf_hi(v[it][i].w));
                }
                float s = s0 + s1;
                s += __shfl_xor_sync(0xffffffffu, s, 1);
                s += __shfl_xor_sync(0xffffffffu, s, 2);
                s += __shfl_xor_sync(0xffffffffu, s, 4);
                if (it == 0 && tid == 0) TL(0, 3);
                const float mean = s * (1.0f / D_);
                float q0 = 0.f, q1 = 0.f;
#pragma unroll
                for (int i = 0; i < 7; i++) {
                    const uint32_t w[4] = {v[it][i].x, v[it][i].y, v[it][i].z, v[it][i].w};
#pragma unroll
                    for (int c = 0; c < 4; c++) {
                        const float d0 = bf_lo(w[c]) - mean, d1 = bf_hi(w[c]) - mean;
                        q0 = fmaf(d0, d0, q0);
                        q1 = fmaf(d1, d1, q1);
                    }
                }
                float q = q0 + q1;
                q += __shfl_xor_sync(0xffffffffu, q, 1);
                q += __shfl_xor_sync(0xffffffffu, q, 2);
                q += __shfl_xor_sync(0xffffffffu, q, 4);
                const float var = rbf(q * (1.0f / D_));
                const float den = rbf(sqrtf(rbf(var + 1e-5f)));
                const float rinv = 1.0f / den;
                const float rhi = rbf(rinv);
                const uint32_t m2 = pack_bf16(mean, mean), rhi2 = pack_bf16(rhi, rhi), rlo2 = pack_bf16(rinv - rhi, rinv - rhi);
                const uint32_t dst = sb + S1_XN + row * 128 + ((l8 ^ (row & 7)) << 4);
#pragma unroll
                for (int i = 0; i < 7; i++) {
                    const uint32_t w[4] = {v[it][i].x, v[it][i].y, v[it][i].z, v[it][i].w};
                    uint32_t o[4];
#pragma unroll
                    for (int c = 0; c < 4; c++) {
                        const uint32_t xc = hsub2(w[c], m2);
                        o[c] = hfma2(xc, rhi2, hmul2(xc, rlo2));
                    }
                    asm volatile("st.shared.v4.b32 [%0], {%1, %2, %3, %4};" ::"r"(dst + i * 16384), "r"(o[0]), "r"(o[1]), "r"(o[2]), "r"(o[3]) : "memory");
                }
            }
        }
        fence_async();
        __syncthreads();
        if (tid == 0) TL(0, 2);
    }

    if (warp >= 8) {
        asm volatile("setmaxnreg.dec.sync.aligned.u32 40;");
        if (warp == 8) {
            if (lane == 0) {
                int st = 0;
                uint32_t ph = 0;
                for (int p = 0; p < npass; p++) {
                    const int slab = pass_slab(j, p);
                    for (int kb = p ? 0 : S1_STAGES; kb < 7; kb++) {
                        mbar_wait(sb + BAR_E1 + 8 * st, ph);
                        const uint32_t dst = sb + S1_B + st * 16384 + rank * 8192;
                        const uint32_t fb = sb + BAR_F1 + 8 * st;
                        mbar_expect(fb, 16384);
                        if (slab >= 0) {
                            tma_load_mc(dst, rank ? &tm.wu : &tm.wg, fb, slab * 64, kb * 64);
                        } else {
                            const int a = 2 * j + rank;
                            tma_load_mc(dst, a < 7 ? &tm.hre : &tm.him, fb, kb * 64, (a < 7 ? a : a - 7) * 64);
                        }
                        if (++st == S1_STAGES) { st = 0; ph ^= 1; }
                    }
                }
                if (part < 3) {
                    mbar_wait(sb + BAR_S1DONE, 0);
                    TL(0, 24);
                    st = 0; ph = 1;
                    if (part < 2) {
                        const CUtensorMap* ma = part ? &tm.sim : &tm.sre;
                        for (int g = 0; g < 32; g++) {
                            mbar_wait(sb + BAR_E2 + 8 * st, ph);
                            const uint32_t dst = sb + st * Y_STAGE;
                            const uint32_t fb = sb + BAR_F2 + 8 * st;
                            mbar_expect(fb, Y_STAGE);
                            tma_load(dst, ma, fb, g * 64, rb * 128);
                            dep_wait(sb, (g >> 1) + 1);
                            tma_load_mc(dst + 16384 + rank * 14336, &tm.abT, fb, g * 64, part * 448 + n * 224 + rank * 112);
                            if (++st == Y_STAGES) { st = 0; ph ^= 1; }
                        }
                    } else {
                        for (int g = 0; g < 28; g++) {
                            mbar_wait(sb + BAR_E2 + 8 * st, ph);
                            const uint32_t dst = sb + st * F_STAGE;
                            const uint32_t fb = sb + BAR_F2 + 8 * st;
                            mbar_expect(fb, F_STAGE);
                            tma_load_mc(dst + 16384 + (2 * rank) * 8192, &tm.wd, fb, n * 224 + (2 * rank) * 64, g * 64);
                            tma_load_mc(dst + 16384 + (2 * rank + 1) * 8192, &tm.wd, fb, n * 224 + (2 * rank + 1) * 64, g * 64);
                            dep_wait(sb, g + 1);
                            tma_load(dst, &tm.h, fb, g * 64, rb * 128);
                            if (++st == F_STAGES) { st = 0; ph ^= 1; }
                        }
                    }
                }
            }
        } else if (warp == 9) {
            if (part < 3) {
                if (part < 2 && lane < 16) {
                    tma_prefetch(part ? &tm.sim : &tm.sre, (2 * lane + n) * 64, rb * 128);
                }
                const int ndep = part < 2 ? 16 : 29;
                const unsigned int epoch = *(volatile unsigned int*)&g_fl.done / gridDim.x + 1;
                const unsigned int* f = part < 2 ? &g_fl.ab[lane & 15] : (lane < 28 ? &g_fl.h[rb * 28 + lane] : &g_fl.y[rb * 2 + n]);
                const unsigned int target = (part < 2 ? 7 : (lane < 27 ? 1 : (lane == 27 ? 2 : 16))) * epoch;
                bool ok = lane >= ndep;
                int published = 0;
                for (int spins = 0; published < ndep && spins < (1 << 22); spins++) {
                    if (!ok) {
                        unsigned int v;
                        asm volatile("ld.acquire.gpu.global.u32 %0, [%1];" : "=r"(v) : "l"(f) : "memory");
                        ok = (int)(v - target) >= 0;
                    }
                    const unsigned int m = __ballot_sync(0xffffffffu, ok);
                    const int cnt = min(__ffs(~m) - 1, ndep);
                    if (m == 0xffffffffu || cnt > published) {
                        published = (m == 0xffffffffu) ? ndep : cnt;
                        fence_async_all();
                        __syncwarp();
                        if (lane == 0) asm volatile("st.release.cta.shared.u32 [%0], %1;" ::"r"(sb + DEP_CNT), "r"(published) : "memory");
                    }
                }
                if (published < ndep && lane == 0)
                    asm volatile("st.release.cta.shared.u32 [%0], %1;" ::"r"(sb + DEP_CNT), "r"(ndep) : "memory");
            }
        } else if (warp == 10) {
            if (lane == 0) {
                for (int p = 0; p < npass; p++) {
                    const int slab = pass_slab(j, p);
                    mbar_wait(sb + BAR_SF, p & 1);
                    if (slab == 27) tma_store(&tm.h64, sb + STG, slab * 64, rb * 128 + n * 64);
                    else if (slab >= 0) tma_store(&tm.h, sb + STG, slab * 64, rb * 128);
                    else tma_store(&tm.abT_st, sb + STG, rb * 128, j * 128);
                    bulk_commit();
                    bulk_wait_read0();
                    asm volatile("st.release.cta.shared.u32 [%0], %1;" ::"r"(sb + SE_CNT), "r"(p + 1) : "memory");
                    bulk_wait0();
                    fence_async_all();
                    if (slab < 0) __threadfence();
                    flag_add(slab >= 0 ? &g_fl.h[rb * 28 + slab] : &g_fl.ab[rb]);
                }
            }
        }
        __syncwarp();
    } else {
        asm volatile("setmaxnreg.inc.sync.aligned.u32 232;");
        const int wg = warp >> 2, wl = warp & 3, wtid = tid & 127;
        const int qd = lane & 3;
        {
            float acc[2][64];
            for (int p = wg; p < npass; p += 2) {
                const int slab = pass_slab(j, p);
                if (p > 0) bar_sync(4 + (p & 1), 256);
                const int handoff = (p + 1 < npass) ? 4 + ((p + 1) & 1) : 0;
                if (slab == 27) s1_mainloop<2>(acc, sb, p, lane, handoff, n);
                else if (slab >= 0) s1_mainloop<1>(acc, sb, p, lane, handoff);
                else s1_mainloop<0>(acc, sb, p, lane, handoff);
                if (p + 2 >= npass && part < 3 && lane == 0) mbar_arrive_both(sb + BAR_S1DONE);
                if (wtid == 0 && p < 4) TL(0, 4 + p);

                const uint32_t srow = sb + STG + (wl * 16 + (lane & 7) + ((lane >> 3) & 1) * 8) * 128;
                if (slab >= 0) {
                    uint32_t hv[2][16];
#pragma unroll
                    for (int mh = 0; mh < 2; mh++) {
                        if (mh == 0 || slab != 27) {
#pragma unroll
                            for (int i = 0; i < 16; i++) {
                                const uint32_t g2 = pack_bf16(acc[mh][2 * i], acc[mh][2 * i + 1]);
                                const uint32_t u2 = pack_bf16(acc[mh][32 + 2 * i], acc[mh][32 + 2 * i + 1]);
                                const uint32_t a2 = pack_bf16(gelu_tanh(bf_lo(g2)), gelu_tanh(bf_hi(g2)));
                                hv[mh][i] = hmul2(a2, u2);
                            }
                        }
                    }
                    cnt_wait(sb + SE_CNT, p);
#pragma unroll
                    for (int mh = 0; mh < 2; mh++) {
                        if (mh == 0 || slab != 27) {
#pragma unroll
                            for (int jj = 0; jj < 8; jj += 2)
                                stmat4(srow + mh * 8192 + (((jj + (lane >> 4)) ^ (lane & 7)) << 4),
                                       hv[mh][2 * jj], hv[mh][2 * jj + 1], hv[mh][2 * jj + 2], hv[mh][2 * jj + 3]);
                        }
                    }
                } else {
#pragma unroll
                    for (int mh = 0; mh < 2; mh++) {
#pragma unroll
                        for (int jj = 0; jj < 8; jj += 2) {
                            const int o = jj * 4;
                            stmat4(srow + mh * 8192 + (((jj + (lane >> 4)) ^ (lane & 7)) << 4),
                                   pack_bf16(acc[mh][o], acc[mh][o + 1]), pack_bf16(acc[mh][o + 2], acc[mh][o + 3]),
                                   pack_bf16(acc[mh][o + 4], acc[mh][o + 5]), pack_bf16(acc[mh][o + 6], acc[mh][o + 7]));
                        }
                    }
                    __nv_bfloat16* dst = g_abT + (size_t)(j * 128 + wl * 16 + (lane >> 2)) * ABP + rb * 128 + 64 + qd * 8;
#pragma unroll
                    for (int mh = 0; mh < 2; mh++) {
#pragma unroll
                        for (int hh = 0; hh < 2; hh++) {
#pragma unroll
                            for (int g4 = 0; g4 < 2; g4++) {
                                uint32_t r[4];
#pragma unroll
                                for (int t = 0; t < 4; t++) {
                                    const int o = 32 + (g4 * 4 + t) * 4 + hh * 2;
                                    r[t] = pack_bf16(acc[mh][o], acc[mh][o + 1]);
                                }
                                quad_transpose(r, qd);
                                __stcg(reinterpret_cast<uint4*>(dst + (size_t)(mh * 64 + hh * 8) * ABP + g4 * 32), make_uint4(r[0], r[1], r[2], r[3]));
                            }
                        }
                    }
                }
                fence_async();
                __syncwarp();
                if (lane == 0) mbar_arrive(sb + BAR_SF);
                if (wtid == 0 && p < 4) TL(0, 10 + p);
            }
        }
        if (wtid == 0) TL(0, 20 + wg);
        if (part < 3) {
            {
                float acc[112];
                const size_t base = (size_t)(rb * 128 + wg * 64 + wl * 16 + (lane >> 2)) * D_ + n * 224 + qd * 8;
                if (part < 2) {
                    s2_mainloop<0>(acc, sb, wg, lane);
                    if (tid == 0) TL(0, 25);
                    uint4* dst = g_y + (size_t)((part * 32 + rb * 2 + n) * 14) * 256 + tid;
#pragma unroll
                    for (int i = 0; i < 14; i++)
                        __stcg(dst + i * 256, make_uint4(pack_bf16(acc[8 * i], acc[8 * i + 1]), pack_bf16(acc[8 * i + 2], acc[8 * i + 3]),
                                                         pack_bf16(acc[8 * i + 4], acc[8 * i + 5]), pack_bf16(acc[8 * i + 6], acc[8 * i + 7])));
                    __threadfence();
                    __syncwarp();
                    if (lane == 0) flag_add(&g_fl.y[rb * 2 + n]);
                } else {
                    uint4 xv[14];
#pragma unroll
                    for (int i = 0; i < 14; i++)
                        xv[i] = __ldg(reinterpret_cast<const uint4*>(pt.x + base + (i / 7) * 8 * D_ + (i % 7) * 32));
                    s2_mainloop<1>(acc, sb, wg, lane);
                    if (tid == 0) TL(0, 25);
                    dep_wait(sb, 29);
                    if (tid == 0) TL(0, 26);
                    const uint4* ysrc = g_y + (size_t)((rb * 2 + n) * 14) * 256 + tid;
                    uint4 yr[14], yi[14];
#pragma unroll
                    for (int i = 0; i < 14; i++) yr[i] = __ldcg(ysrc + i * 256);
                    uint32_t sg[56];
#pragma unroll
                    for (int i = 0; i < 56; i++) {
                        const uint32_t f2 = pack_bf16(acc[2 * i], acc[2 * i + 1]);
                        sg[i] = pack_bf16(silu(bf_lo(f2)), silu(bf_hi(f2)));
                    }
#pragma unroll
                    for (int i = 0; i < 14; i++) yi[i] = __ldcg(ysrc + (32 * 14 + i) * 256);
#pragma unroll
                    for (int i = 0; i < 14; i++) {
                        sg[4 * i + 0] = hmul2(hsub2(yr[i].x, yi[i].x), sg[4 * i + 0]);
                        sg[4 * i + 1] = hmul2(hsub2(yr[i].y, yi[i].y), sg[4 * i + 1]);
                        sg[4 * i + 2] = hmul2(hsub2(yr[i].z, yi[i].z), sg[4 * i + 2]);
                        sg[4 * i + 3] = hmul2(hsub2(yr[i].w, yi[i].w), sg[4 * i + 3]);
                    }
#pragma unroll
                    for (int hh = 0; hh < 2; hh++) {
#pragma unroll
                        for (int g4 = 0; g4 < 7; g4++) {
                            uint32_t r[4];
#pragma unroll
                            for (int t = 0; t < 4; t++) r[t] = sg[(g4 * 4 + t) * 2 + hh];
                            quad_transpose(r, qd);
                            const uint4 xx = xv[hh * 7 + g4];
                            *reinterpret_cast<uint4*>(pt.out + base + hh * 8 * D_ + g4 * 32) =
                                make_uint4(hadd2(xx.x, r[0]), hadd2(xx.y, r[1]), hadd2(xx.z, r[2]), hadd2(xx.w, r[3]));
                        }
                    }
                }
            }
        }
    }
    if (tid == 0) TL(0, 29);
    __syncthreads();
    if (tid == 0) {
        TL(0, 30);
        atomicAdd(&g_fl.done, 1u);
    }
}

typedef CUresult (*EncFn)(CUtensorMap*, CUtensorMapDataType, cuuint32_t, void*, const cuuint64_t*, const cuuint64_t*,
                          const cuuint32_t*, const cuuint32_t*, CUtensorMapInterleave, CUtensorMapSwizzle,
                          CUtensorMapL2promotion, CUtensorMapFloatOOBfill);

void make_map(EncFn enc, CUtensorMap* m, const void* ptr, int rows, int cols, int box_rows, int box_cols, int pitch = 0) {
    const bool swz = true;
    cuuint64_t gd[2] = {(cuuint64_t)cols, (cuuint64_t)rows};
    cuuint64_t gs[1] = {(cuuint64_t)(pitch ? pitch : cols) * 2};
    cuuint32_t bx[2] = {(cuuint32_t)box_cols, (cuuint32_t)box_rows};
    cuuint32_t es[2] = {1, 1};
    enc(m, CU_TENSOR_MAP_DATA_TYPE_BFLOAT16, 2, const_cast<void*>(ptr), gd, gs, bx, es, CU_TENSOR_MAP_INTERLEAVE_NONE,
        swz ? CU_TENSOR_MAP_SWIZZLE_128B : CU_TENSOR_MAP_SWIZZLE_NONE, CU_TENSOR_MAP_L2_PROMOTION_L2_128B,
        CU_TENSOR_MAP_FLOAT_OOB_FILL_NONE);
}

}

extern "C" void kernel_launch(void* const* d_in, const int* in_sizes, int n_in, void* d_out, int out_size) {
    Ptrs pt;
    pt.x = (const __nv_bfloat16*)d_in[0];
    pt.hre = (const __nv_bfloat16*)d_in[3];
    pt.him = (const __nv_bfloat16*)d_in[4];
    pt.wg = (const __nv_bfloat16*)d_in[6];
    pt.wu = (const __nv_bfloat16*)d_in[7];
    pt.wd = (const __nv_bfloat16*)d_in[8];
    pt.out = (__nv_bfloat16*)d_out;

    void* fn = nullptr;
    cudaDriverEntryPointQueryResult qr;
    cudaGetDriverEntryPoint("cuTensorMapEncodeTiled", &fn, cudaEnableDefault, &qr);
    EncFn enc = (EncFn)fn;
    void *p_abT, *p_h;
    cudaGetSymbolAddress(&p_abT, g_abT);
    cudaGetSymbolAddress(&p_h, g_h);

    Maps tm;
    make_map(enc, &tm.wg, d_in[6], D_, F_, 64, 64);
    make_map(enc, &tm.wu, d_in[7], D_, F_, 64, 64);
    make_map(enc, &tm.hre, d_in[3], D_, D_, 64, 64);
    make_map(enc, &tm.him, d_in[4], D_, D_, 64, 64);
    make_map(enc, &tm.h, p_h, S_, F_, 128, 64);
    make_map(enc, &tm.h64, p_h, S_, F_, 64, 64);
    make_map(enc, &tm.abT, p_abT, 896, S_, 112, 64, ABP);
    make_map(enc, &tm.abT_st, p_abT, 896, S_, 128, 64, ABP);
    make_map(enc, &tm.sre, d_in[1], S_, S_, 128, 64);
    make_map(enc, &tm.sim, d_in[2], S_, S_, 128, 64);
    make_map(enc, &tm.wd, d_in[8], F_, D_, 64, 64);

    cudaFuncSetAttribute(fused_kernel, cudaFuncAttributeMaxDynamicSharedMemorySize, SMEM_BYTES);

    cudaLaunchAttribute at[1];
    at[0].id = cudaLaunchAttributeClusterDimension;
    at[0].val.clusterDim.x = 2; at[0].val.clusterDim.y = 1; at[0].val.clusterDim.z = 1;
    cudaLaunchConfig_t cfg = {};
    cfg.gridDim = dim3(128); cfg.blockDim = dim3(384); cfg.stream = cudaStreamPerThread;
    cfg.attrs = at; cfg.numAttrs = 1;
    cfg.dynamicSmemBytes = SMEM_BYTES;
    cudaLaunchKernelEx(&cfg, fused_kernel, pt, tm);
}
```

```cpp
#include <cuda_runtime.h>
#include <cuda_bf16.h>
#include <cuda.h>
#include <stdint.h>

namespace {

constexpr int S_ = 2048, D_ = 448, F_ = 1792;

constexpr int ABP = 2048 + 64;
__device__ __align__(1024) __nv_bfloat16 g_abT[896 * ABP];
__device__ __align__(1024) __nv_bfloat16 g_h[2048 * 1792];
__device__ __align__(1024) uint4 g_y[2 * 32 * 14 * 256];
struct Flags {
    unsigned int ab[16];
    unsigned int h[16 * 28];
    unsigned int y[32];
    unsigned int done;
};
__device__ Flags g_fl;

#define TL(k, i) do {} while (0)
__device__ __forceinline__ uint32_t s2u(const void* p) { return (uint32_t)__cvta_generic_to_shared(p); }
__device__ __forceinline__ void mbar_init(uint32_t b, int c) {
    asm volatile("mbarrier.init.shared::cta.b64 [%0], %1;" ::"r"(b), "r"(c));
}
__device__ __forceinline__ void mbar_expect(uint32_t b, uint32_t bytes) {
    asm volatile("mbarrier.arrive.expect_tx.shared::cta.b64 _, [%0], %1;" ::"r"(b), "r"(bytes) : "memory");
}
__device__ __forceinline__ void mbar_wait(uint32_t b, uint32_t ph) {
    uint32_t ok;
    do {
        asm volatile("{\n.reg .pred p;\nmbarrier.try_wait.parity.shared::cta.b64 p, [%1], %2;\nselp.u32 %0, 1, 0, p;\n}"
                     : "=r"(ok) : "r"(b), "r"(ph) : "memory");
    } while (!ok);
}
__device__ __forceinline__ void mbar_arrive_both(uint32_t b) {
    asm volatile("{\n.reg .b32 r0, r1;\n"
                 "mapa.shared::cluster.u32 r0, %0, 0;\n"
                 "mapa.shared::cluster.u32 r1, %0, 1;\n"
                 "mbarrier.arrive.shared::cluster.b64 _, [r0];\n"
                 "mbarrier.arrive.shared::cluster.b64 _, [r1];\n}"
                 ::"r"(b) : "memory");
}
__device__ __forceinline__ void tma_load(uint32_t dst, const CUtensorMap* m, uint32_t bar, int c0, int c1) {
    asm volatile("cp.async.bulk.tensor.2d.shared::cluster.global.mbarrier::complete_tx::bytes [%0], [%1, {%3, %4}], [%2];"
                 ::"r"(dst), "l"(m), "r"(bar), "r"(c0), "r"(c1) : "memory");
}
__device__ __forceinline__ void tma_load_mc(uint32_t dst, const CUtensorMap* m, uint32_t bar, int c0, int c1) {
    asm volatile("cp.async.bulk.tensor.2d.shared::cluster.global.mbarrier::complete_tx::bytes.multicast::cluster [%0], [%1, {%3, %4}], [%2], %5;"
                 ::"r"(dst), "l"(m), "r"(bar), "r"(c0), "r"(c1), "h"((uint16_t)3) : "memory");
}
__device__ __forceinline__ void tma_store(const CUtensorMap* m, uint32_t src, int c0, int c1) {
    asm volatile("cp.async.bulk.tensor.2d.global.shared::cta.bulk_group [%0, {%2, %3}], [%1];"
                 ::"l"(m), "r"(src), "r"(c0), "r"(c1) : "memory");
}
__device__ __forceinline__ void bulk_commit() { asm volatile("cp.async.bulk.commit_group;" ::: "memory"); }
__device__ __forceinline__ void bulk_wait_read0() { asm volatile("cp.async.bulk.wait_group.read 0;" ::: "memory"); }
__device__ __forceinline__ void bulk_wait0() { asm volatile("cp.async.bulk.wait_group 0;" ::: "memory"); }
__device__ __forceinline__ void fence_async() { asm volatile("fence.proxy.async.shared::cta;" ::: "memory"); }
__device__ __forceinline__ void fence_async_all() { asm volatile("fence.proxy.async;" ::: "memory"); }
__device__ __forceinline__ void cluster_sync() {
    asm volatile("barrier.cluster.arrive.release.aligned;\nbarrier.cluster.wait.acquire.aligned;" ::: "memory");
}
__device__ __forceinline__ void bar_sync(int id, int n) { asm volatile("bar.sync %0, %1;" ::"r"(id), "r"(n) : "memory"); }
__device__ __forceinline__ void wg_arrive() { asm volatile("wgmma.fence.sync.aligned;" ::: "memory"); }
__device__ __forceinline__ void wg_commit() { asm volatile("wgmma.commit_group.sync.aligned;" ::: "memory"); }
template <int N> __device__ __forceinline__ void wg_wait() { asm volatile("wgmma.wait_group.sync.aligned %0;" ::"n"(N) : "memory"); }
__device__ __forceinline__ void stmat4(uint32_t a, uint32_t r0, uint32_t r1, uint32_t r2, uint32_t r3) {
    asm volatile("stmatrix.sync.aligned.m8n8.x4.shared.b16 [%0], {%1, %2, %3, %4};" ::"r"(a), "r"(r0), "r"(r1), "r"(r2), "r"(r3) : "memory");
}
__device__ __forceinline__ void stmat4t(uint32_t a, uint32_t r0, uint32_t r1, uint32_t r2, uint32_t r3) {
    asm volatile("stmatrix.sync.aligned.m8n8.x4.trans.shared.b16 [%0], {%1, %2, %3, %4};" ::"r"(a), "r"(r0), "r"(r1), "r"(r2), "r"(r3) : "memory");
}
__device__ __forceinline__ void ldmat4(uint32_t a, uint32_t (&r)[4]) {
    asm volatile("ldmatrix.sync.aligned.m8n8.x4.shared.b16 {%0, %1, %2, %3}, [%4];"
                 : "=r"(r[0]), "=r"(r[1]), "=r"(r[2]), "=r"(r[3]) : "r"(a) : "memory");
}
__device__ __forceinline__ void flag_add(unsigned int* f) {
    asm volatile("red.release.gpu.global.add.u32 [%0], 1;" ::"l"(f) : "memory");
}
__device__ __forceinline__ void flag_wait(const unsigned int* f, unsigned int target) {
    unsigned int v;
    int spins = 0;
    while (true) {
        asm volatile("ld.acquire.gpu.global.u32 %0, [%1];" : "=r"(v) : "l"(f) : "memory");
        if ((int)(v - target) >= 0 || ++spins > (1 << 22)) break;
    }
}
__device__ __forceinline__ void quad_transpose(uint32_t (&r)[4], int q) {
    const bool o1 = q & 1, o2 = q & 2;
    uint32_t a = o1 ? r[0] : r[1], b = o1 ? r[2] : r[3];
    a = __shfl_xor_sync(0xffffffffu, a, 1);
    b = __shfl_xor_sync(0xffffffffu, b, 1);
    if (o1) { r[0] = a; r[2] = b; } else { r[1] = a; r[3] = b; }
    a = o2 ? r[0] : r[2]; b = o2 ? r[1] : r[3];
    a = __shfl_xor_sync(0xffffffffu, a, 2);
    b = __shfl_xor_sync(0xffffffffu, b, 2);
    if (o2) { r[0] = a; r[1] = b; } else { r[2] = a; r[3] = b; }
}
__device__ __forceinline__ uint32_t movmat_t(uint32_t v) {
    uint32_t r;
    asm volatile("movmatrix.sync.aligned.m8n8.trans.b16 %0, %1;" : "=r"(r) : "r"(v));
    return r;
}
__device__ __forceinline__ uint64_t mkdesc(uint32_t addr, uint32_t lbo, uint32_t sbo) {
    return (uint64_t)((addr & 0x3FFFF) >> 4) | ((uint64_t)(lbo >> 4) << 16) | ((uint64_t)(sbo >> 4) << 32) | (1ull << 62);
}
__device__ __forceinline__ uint32_t pack_bf16(float lo, float hi) {
    uint32_t r;
    asm("cvt.rn.bf16x2.f32 %0, %1, %2;" : "=r"(r) : "f"(hi), "f"(lo));
    return r;
}
__device__ __forceinline__ uint32_t hsub2(uint32_t a, uint32_t b) { uint32_t r; asm("sub.rn.bf16x2 %0, %1, %2;" : "=r"(r) : "r"(a), "r"(b)); return r; }
__device__ __forceinline__ uint32_t hadd2(uint32_t a, uint32_t b) { uint32_t r; asm("add.rn.bf16x2 %0, %1, %2;" : "=r"(r) : "r"(a), "r"(b)); return r; }
__device__ __forceinline__ uint32_t hmul2(uint32_t a, uint32_t b) { uint32_t r; asm("mul.rn.bf16x2 %0, %1, %2;" : "=r"(r) : "r"(a), "r"(b)); return r; }
__device__ __forceinline__ uint32_t hfma2(uint32_t a, uint32_t b, uint32_t c) { uint32_t r; asm("fma.rn.bf16x2 %0, %1, %2, %3;" : "=r"(r) : "r"(a), "r"(b), "r"(c)); return r; }
__device__ __forceinline__ float bf_lo(uint32_t u) { return __uint_as_float(u << 16); }
__device__ __forceinline__ float bf_hi(uint32_t u) { return __uint_as_float(u & 0xffff0000u); }
__device__ __forceinline__ float rbf(float v) { return __bfloat162float(__float2bfloat16_rn(v)); }
__device__ __forceinline__ float tanh_fast(float x) { float r; asm("tanh.approx.f32 %0, %1;" : "=f"(r) : "f"(x)); return r; }
__device__ __forceinline__ float gelu_tanh(float x) {
    float u = x * fmaf(x * x, 0.0356774081f, 0.7978845608f);
    float hx = 0.5f * x;
    return fmaf(hx, tanh_fast(u), hx);
}
__device__ __forceinline__ float silu(float f) { const float hf = 0.5f * f; return fmaf(hf, tanh_fast(hf), hf); }

template <int TB>
__device__ __forceinline__ void wgmma_n128(float (&d)[64], uint64_t da, uint64_t db, int scaleD) {
    asm volatile("{\n.reg .pred p;\nsetp.ne.b32 p, %66, 0;\n"
        "wgmma.mma_async.sync.aligned.m64n128k16.f32.bf16.bf16 {%0, %1, %2, %3, %4, %5, %6, %7, %8, %9, %10, %11, %12, %13, %14, %15, %16, %17, %18, %19, %20, %21, %22, %23, %24, %25, %26, %27, %28, %29, %30, %31, %32, %33, %34, %35, %36, %37, %38, %39, %40, %41, %42, %43, %44, %45, %46, %47, %48, %49, %50, %51, %52, %53, %54, %55, %56, %57, %58, %59, %60, %61, %62, %63}, %64, %65, p, 1, 1, 0, %67;\n}\n"
        : "+f"(d[0]), "+f"(d[1]), "+f"(d[2]), "+f"(d[3]), "+f"(d[4]), "+f"(d[5]), "+f"(d[6]), "+f"(d[7]), "+f"(d[8]), "+f"(d[9]), "+f"(d[10]), "+f"(d[11]), "+f"(d[12]), "+f"(d[13]), "+f"(d[14]), "+f"(d[15]), "+f"(d[16]), "+f"(d[17]), "+f"(d[18]), "+f"(d[19]), "+f"(d[20]), "+f"(d[21]), "+f"(d[22]), "+f"(d[23]), "+f"(d[24]), "+f"(d[25]), "+f"(d[26]), "+f"(d[27]), "+f"(d[28]), "+f"(d[29]), "+f"(d[30]), "+f"(d[31]), "+f"(d[32]), "+f"(d[33]), "+f"(d[34]), "+f"(d[35]), "+f"(d[36]), "+f"(d[37]), "+f"(d[38]), "+f"(d[39]), "+f"(d[40]), "+f"(d[41]), "+f"(d[42]), "+f"(d[43]), "+f"(d[44]), "+f"(d[45]), "+f"(d[46]), "+f"(d[47]), "+f"(d[48]), "+f"(d[49]), "+f"(d[50]), "+f"(d[51]), "+f"(d[52]), "+f"(d[53]), "+f"(d[54]), "+f"(d[55]), "+f"(d[56]), "+f"(d[57]), "+f"(d[58]), "+f"(d[59]), "+f"(d[60]), "+f"(d[61]), "+f"(d[62]), "+f"(d[63])
        : "l"(da), "l"(db), "r"(scaleD), "n"(TB));
}
template <int TB>
__device__ __forceinline__ void wgmma_n224(float (&d)[112], uint64_t da, uint64_t db, int scaleD) {
    asm volatile("{\n.reg .pred p;\nsetp.ne.b32 p, %114, 0;\n"
        "wgmma.mma_async.sync.aligned.m64n224k16.f32.bf16.bf16 {%0, %1, %2, %3, %4, %5, %6, %7, %8, %9, %10, %11, %12, %13, %14, %15, %16, %17, %18, %19, %20, %21, %22, %23, %24, %25, %26, %27, %28, %29, %30, %31, %32, %33, %34, %35, %36, %37, %38, %39, %40, %41, %42, %43, %44, %45, %46, %47, %48, %49, %50, %51, %52, %53, %54, %55, %56, %57, %58, %59, %60, %61, %62, %63, %64, %65, %66, %67, %68, %69, %70, %71, %72, %73, %74, %75, %76, %77, %78, %79, %80, %81, %82, %83, %84, %85, %86, %87, %88, %89, %90, %91, %92, %93, %94, %95, %96, %97, %98, %99, %100, %101, %102, %103, %104, %105, %106, %107, %108, %109, %110, %111}, %112, %113, p, 1, 1, 0, %115;\n}\n"
        : "+f"(d[0]), "+f"(d[1]), "+f"(d[2]), "+f"(d[3]), "+f"(d[4]), "+f"(d[5]), "+f"(d[6]), "+f"(d[7]), "+f"(d[8]), "+f"(d[9]), "+f"(d[10]), "+f"(d[11]), "+f"(d[12]), "+f"(d[13]), "+f"(d[14]), "+f"(d[15]), "+f"(d[16]), "+f"(d[17]), "+f"(d[18]), "+f"(d[19]), "+f"(d[20]), "+f"(d[21]), "+f"(d[22]), "+f"(d[23]), "+f"(d[24]), "+f"(d[25]), "+f"(d[26]), "+f"(d[27]), "+f"(d[28]), "+f"(d[29]), "+f"(d[30]), "+f"(d[31]), "+f"(d[32]), "+f"(d[33]), "+f"(d[34]), "+f"(d[35]), "+f"(d[36]), "+f"(d[37]), "+f"(d[38]), "+f"(d[39]), "+f"(d[40]), "+f"(d[41]), "+f"(d[42]), "+f"(d[43]), "+f"(d[44]), "+f"(d[45]), "+f"(d[46]), "+f"(d[47]), "+f"(d[48]), "+f"(d[49]), "+f"(d[50]), "+f"(d[51]), "+f"(d[52]), "+f"(d[53]), "+f"(d[54]), "+f"(d[55]), "+f"(d[56]), "+f"(d[57]), "+f"(d[58]), "+f"(d[59]), "+f"(d[60]), "+f"(d[61]), "+f"(d[62]), "+f"(d[63]), "+f"(d[64]), "+f"(d[65]), "+f"(d[66]), "+f"(d[67]), "+f"(d[68]), "+f"(d[69]), "+f"(d[70]), "+f"(d[71]), "+f"(d[72]), "+f"(d[73]), "+f"(d[74]), "+f"(d[75]), "+f"(d[76]), "+f"(d[77]), "+f"(d[78]), "+f"(d[79]), "+f"(d[80]), "+f"(d[81]), "+f"(d[82]), "+f"(d[83]), "+f"(d[84]), "+f"(d[85]), "+f"(d[86]), "+f"(d[87]), "+f"(d[88]), "+f"(d[89]), "+f"(d[90]), "+f"(d[91]), "+f"(d[92]), "+f"(d[93]), "+f"(d[94]), "+f"(d[95]), "+f"(d[96]), "+f"(d[97]), "+f"(d[98]), "+f"(d[99]), "+f"(d[100]), "+f"(d[101]), "+f"(d[102]), "+f"(d[103]), "+f"(d[104]), "+f"(d[105]), "+f"(d[106]), "+f"(d[107]), "+f"(d[108]), "+f"(d[109]), "+f"(d[110]), "+f"(d[111])
        : "l"(da), "l"(db), "r"(scaleD), "n"(TB));
}

constexpr int S1_STAGES = 6;
constexpr int S1_XN = 0;
constexpr int S1_B = 7 * 16384;
constexpr int STG = S1_B + S1_STAGES * 16384;
constexpr int Y_STAGES = 4, Y_STAGE = 45056;
constexpr int F_STAGES = 4, F_STAGE = 49152;
constexpr int BAR = STG + 16384;
constexpr int BAR_F1 = BAR, BAR_E1 = BAR + 56, BAR_F2 = BAR + 112, BAR_E2 = BAR + 152, BAR_S1DONE = BAR + 192;
constexpr int BAR_SF = BAR + 208;
constexpr int SE_CNT = BAR + 216;
constexpr int DEP_CNT = BAR + 200;
constexpr int SMEM_BYTES = BAR + 256 + 1024;
constexpr int TPITCH = 464;

__device__ __forceinline__ int n_passes(int j) { return j < 4 ? 2 : (j < 6 ? 4 : 10); }
__device__ __forceinline__ int pass_slab(int j, int p) {
    if (p == 0) return j < 7 ? -1 : 0;
    if (p == 1) return 1 + j;
    if (p < 4) return 4 * p - 3 + j;
    if (p == 9) return 27;
    return 17 + 2 * (p - 4) + (j - 6);
}

template <int TB>
__device__ __forceinline__ void s1_mainloop(float (&acc)[2][64], uint32_t sb, int p, int lane, int handoff, int half = 0) {
    int st = (p * 7) % S1_STAGES;
    uint32_t ph = ((p * 7) / S1_STAGES) & 1;
    int prev = 0;
    uint64_t dx = mkdesc(sb + S1_XN + half * 8192, 16, 1024);
    const uint64_t dw0 = TB ? mkdesc(sb + S1_B, 8192, 1024) : mkdesc(sb + S1_B, 16, 1024);
    const int nrel = lane == 0 ? (handoff ? 7 : 7 - S1_STAGES) : 0;
#pragma unroll 1
    for (int kb = 0; kb < 7; kb++) {
        mbar_wait(sb + BAR_F1 + 8 * st, ph);
        if (kb == 6 && handoff) asm volatile("bar.arrive %0, 256;" ::"r"(handoff) : "memory");
        const uint64_t dw = dw0 + st * 1024;
        wg_arrive();
#pragma unroll
        for (int s = 0; s < 4; s++) {
            if (TB == 2) {
                wgmma_n128<1>(acc[0], dx + s * 2, dw + s * 128, kb | s);
            } else if (TB) {
                wgmma_n128<1>(acc[0], dx + s * 2, dw + s * 128, kb | s);
                wgmma_n128<1>(acc[1], dx + 512 + s * 2, dw + s * 128, kb | s);
            } else {
                wgmma_n128<0>(acc[0], dw + s * 2, dx + s * 2, kb | s);
                wgmma_n128<0>(acc[1], dw + 512 + s * 2, dx + s * 2, kb | s);
            }
        }
        wg_commit();
        wg_wait<1>();
        if (kb > 0 && kb <= nrel) mbar_arrive_both(sb + BAR_E1 + 8 * prev);
        prev = st;
        dx += 1024;
        if (++st == S1_STAGES) { st = 0; ph ^= 1; }
    }
    wg_wait<0>();
    if (nrel == 7) mbar_arrive_both(sb + BAR_E1 + 8 * prev);
}

template <int TB>
__device__ __forceinline__ void s2_mainloop(float (&acc)[112], uint32_t sb, int wg, int lane) {
    constexpr int NST = TB ? F_STAGES : Y_STAGES, SSZ = TB ? F_STAGE : Y_STAGE, NKB = TB ? 28 : 32;
    int st = 0;
    uint32_t ph = 0;
    int prev = 0;
    const uint64_t da0 = mkdesc(sb + wg * 8192, 16, 1024);
    const uint64_t db0 = TB ? mkdesc(sb + 16384, 8192, 1024) : mkdesc(sb + 16384, 16, 1024);
#pragma unroll 1
    for (int i = 0; i < NKB; i++) {
        mbar_wait(sb + BAR_F2 + 8 * st, ph);
        if (threadIdx.x == 0 && (i == 0 || i == 8 || i == 16 || i == 24 || i == 26 || i == 27)) TL(0, 14 + (i == 26 ? 4 : (i == 27 ? 5 : i / 8)));
        const uint64_t da = da0 + st * (SSZ / 16), db = db0 + st * (SSZ / 16);
        wg_arrive();
#pragma unroll
        for (int s = 0; s < 4; s++) wgmma_n224<TB>(acc, da + s * 2, db + s * (TB ? 128 : 2), i | s);
        wg_commit();
        wg_wait<1>();
        if (i > 0 && i <= NKB - NST && lane == 0) mbar_arrive_both(sb + BAR_E2 + 8 * prev);
        prev = st;
        if (++st == NST) { st = 0; ph ^= 1; }
    }
    wg_wait<0>();
}

struct Maps {
    CUtensorMap wg, wu, hre, him, h, h64, abT, abT_st, sre, sim, wd;
};
struct Ptrs {
    const __nv_bfloat16 *x, *hre, *him, *wg, *wu, *wd;
    __nv_bfloat16* out;
};
__device__ __forceinline__ void mbar_arrive(uint32_t b) {
    asm volatile("mbarrier.arrive.shared::cta.b64 _, [%0];" ::"r"(b) : "memory");
}
__device__ __forceinline__ void l2_prefetch(const void* p, uint32_t bytes) {
    asm volatile("cp.async.bulk.prefetch.L2.global [%0], %1;" ::"l"(p), "r"(bytes) : "memory");
}
__device__ __forceinline__ void tma_prefetch(const CUtensorMap* m, int c0, int c1) {
    asm volatile("cp.async.bulk.prefetch.tensor.2d.L2.global.tile [%0, {%1, %2}];" ::"l"(m), "r"(c0), "r"(c1) : "memory");
}

__device__ __forceinline__ void cnt_wait(uint32_t addr, uint32_t need) {
    uint32_t v;
    do { asm volatile("ld.acquire.cta.shared.u32 %0, [%1];" : "=r"(v) : "r"(addr) : "memory"); } while (v < need);
}
__device__ __forceinline__ void dep_wait(uint32_t sb, uint32_t need) { cnt_wait(sb + DEP_CNT, need); }

__global__ void __launch_bounds__(384, 1)
fused_kernel(const __grid_constant__ Ptrs pt, const __grid_constant__ Maps tm) {
    extern __shared__ unsigned char smem_raw[];
    const uint32_t sb = (s2u(smem_raw) + 1023) & ~1023u;
    const int tid = threadIdx.x, lane = tid & 31;
    const int warp = __shfl_sync(0xffffffffu, tid >> 5, 0);
    const int rank = blockIdx.x & 1;
    const int cid = blockIdx.x >> 1;
    const int j = cid & 7;
    const int rb = (cid >> 3) * 2 + rank;
    const int npass = n_passes(j);
    const int n = j & 1;
    const int part = j >> 1;

    {
        const int l8 = lane & 7, sub = lane >> 3;
        uint4 v[3][7];
#pragma unroll
        for (int it = 0; it < 3; it++) {
            const int qd = warp + 12 * it;
            if (qd < 32) {
                const uint4* src = reinterpret_cast<const uint4*>(pt.x + (size_t)(rb * 128 + qd * 4 + sub) * D_) + l8;
#pragma unroll
                for (int i = 0; i < 7; i++) v[it][i] = __ldg(src + i * 8);
            }
        }
        if (tid == 256) {
            TL(0, 0);
            for (int i = 0; i < S1_STAGES; i++) { mbar_init(sb + BAR_F1 + 8 * i, 1); mbar_init(sb + BAR_E1 + 8 * i, 8); }
            for (int i = 0; i < Y_STAGES; i++) { mbar_init(sb + BAR_F2 + 8 * i, 1); mbar_init(sb + BAR_E2 + 8 * i, 16); }
            mbar_init(sb + BAR_S1DONE, 16);
            mbar_init(sb + BAR_SF, 4);
            asm volatile("st.shared.u32 [%0], %1;" ::"r"(sb + SE_CNT), "r"(0) : "memory");
            asm volatile("st.shared.u32 [%0], %1;" ::"r"(sb + DEP_CNT), "r"(0) : "memory");
            asm volatile("fence.mbarrier_init.release.cluster;" ::: "memory");
        }
        __syncwarp();
        asm volatile("barrier.cluster.arrive.relaxed.aligned;\nbarrier.cluster.wait.aligned;" ::: "memory");
        if (tid == 256) {
            const int slab = pass_slab(j, 0);
            for (int kb = 0; kb < S1_STAGES; kb++) {
                const uint32_t dst = sb + S1_B + kb * 16384 + rank * 8192;
                const uint32_t fb = sb + BAR_F1 + 8 * kb;
                mbar_expect(fb, 16384);
                if (slab >= 0) {
                    tma_load_mc(dst, rank ? &tm.wu : &tm.wg, fb, slab * 64, kb * 64);
                } else {
                    const int a = 2 * j + rank;
                    tma_load_mc(dst, a < 7 ? &tm.hre : &tm.him, fb, kb * 64, (a < 7 ? a : a - 7) * 64);
                }
            }
            const int b = blockIdx.x;
            l2_prefetch((const char*)pt.hre + b * 3136, 3136);
            l2_prefetch((const char*)pt.him + b * 3136, 3136);
            l2_prefetch((const char*)pt.wg + b * 12544, 12544);
            l2_prefetch((const char*)pt.wu + b * 12544, 12544);
            l2_prefetch((const char*)pt.wd + b * 12544, 12544);
        }
        __syncwarp();
        if (tid == 0) TL(0, 1);
#pragma unroll
        for (int it = 0; it < 3; it++) {
            const int qd = warp + 12 * it;
            if (qd < 32) {
                const int row = qd * 4 + sub;
                float s0 = 0.f, s1 = 0.f, q0 = 0.f, q1 = 0.f;
#pragma unroll
                for (int i = 0; i < 7; i++) {
                    const uint32_t w[4] = {v[it][i].x, v[it][i].y, v[it][i].z, v[it][i].w};
#pragma unroll
                    for (int c = 0; c < 4; c++) {
                        const float d0 = bf_lo(w[c]), d1 = bf_hi(w[c]);
                        s0 += d0; s1 += d1;
                        q0 = fmaf(d0, d0, q0);
                        q1 = fmaf(d1, d1, q1);
                    }
                }
                float s = s0 + s1, q = q0 + q1;
#pragma unroll
                for (int o = 1; o < 8; o <<= 1) {
                    s += __shfl_xor_sync(0xffffffffu, s, o);
                    q += __shfl_xor_sync(0xffffffffu, q, o);
                }
                if (it == 0 && tid == 0) TL(0, 3);
                const float mean = s * (1.0f / D_);
                const float var = rbf(fmaxf(fmaf(-mean, mean, q * (1.0f / D_)), 0.f));
                const float den = rbf(sqrtf(rbf(var + 1e-5f)));
                const float rinv = 1.0f / den;
                const float rhi = rbf(rinv);
                const uint32_t m2 = pack_bf16(mean, mean), rhi2 = pack_bf16(rhi, rhi), rlo2 = pack_bf16(rinv - rhi, rinv - rhi);
                const uint32_t dst = sb + S1_XN + row * 128 + ((l8 ^ (row & 7)) << 4);
#pragma unroll
                for (int i = 0; i < 7; i++) {
                    const uint32_t w[4] = {v[it][i].x, v[it][i].y, v[it][i].z, v[it][i].w};
                    uint32_t o[4];
#pragma unroll
                    for (int c = 0; c < 4; c++) {
                        const uint32_t xc = hsub2(w[c], m2);
                        o[c] = hfma2(xc, rhi2, hmul2(xc, rlo2));
                    }
                    asm volatile("st.shared.v4.b32 [%0], {%1, %2, %3, %4};" ::"r"(dst + i * 16384), "r"(o[0]), "r"(o[1]), "r"(o[2]), "r"(o[3]) : "memory");
                }
            }
        }
        fence_async();
        __syncthreads();
        if (tid == 0) TL(0, 2);
    }

    if (warp >= 8) {
        asm volatile("setmaxnreg.dec.sync.aligned.u32 40;");
        if (warp == 8) {
            if (lane == 0) {
                int st = 0;
                uint32_t ph = 0;
                for (int p = 0; p < npass; p++) {
                    const int slab = pass_slab(j, p);
                    for (int kb = p ? 0 : S1_STAGES; kb < 7; kb++) {
                        mbar_wait(sb + BAR_E1 + 8 * st, ph);
                        const uint32_t dst = sb + S1_B + st * 16384 + rank * 8192;
                        const uint32_t fb = sb + BAR_F1 + 8 * st;
                        mbar_expect(fb, 16384);
                        if (slab >= 0) {
                            tma_load_mc(dst, rank ? &tm.wu : &tm.wg, fb, slab * 64, kb * 64);
                        } else {
                            const int a = 2 * j + rank;
                            tma_load_mc(dst, a < 7 ? &tm.hre : &tm.him, fb, kb * 64, (a < 7 ? a : a - 7) * 64);
                        }
                        if (++st == S1_STAGES) { st = 0; ph ^= 1; }
                    }
                }
                if (part < 3) {
                    mbar_wait(sb + BAR_S1DONE, 0);
                    TL(0, 24);
                    st = 0; ph = 1;
                    if (part < 2) {
                        const CUtensorMap* ma = part ? &tm.sim : &tm.sre;
                        for (int g = 0; g < 32; g++) {
                            mbar_wait(sb + BAR_E2 + 8 * st, ph);
                            const uint32_t dst = sb + st * Y_STAGE;
                            const uint32_t fb = sb + BAR_F2 + 8 * st;
                            mbar_expect(fb, Y_STAGE);
                            tma_load(dst, ma, fb, g * 64, rb * 128);
                            dep_wait(sb, (g >> 1) + 1);
                            tma_load_mc(dst + 16384 + rank * 14336, &tm.abT, fb, g * 64, part * 448 + n * 224 + rank * 112);
                            if (++st == Y_STAGES) { st = 0; ph ^= 1; }
                        }
                    } else {
                        for (int g = 0; g < 28; g++) {
                            mbar_wait(sb + BAR_E2 + 8 * st, ph);
                            const uint32_t dst = sb + st * F_STAGE;
                            const uint32_t fb = sb + BAR_F2 + 8 * st;
                            mbar_expect(fb, F_STAGE);
                            tma_load_mc(dst + 16384 + (2 * rank) * 8192, &tm.wd, fb, n * 224 + (2 * rank) * 64, g * 64);
                            tma_load_mc(dst + 16384 + (2 * rank + 1) * 8192, &tm.wd, fb, n * 224 + (2 * rank + 1) * 64, g * 64);
                            dep_wait(sb, g + 1);
                            tma_load(dst, &tm.h, fb, g * 64, rb * 128);
                            if (++st == F_STAGES) { st = 0; ph ^= 1; }
                        }
                    }
                }
            }
        } else if (warp == 9) {
            if (part < 3) {
                if (part < 2 && lane < 16) {
                    tma_prefetch(part ? &tm.sim : &tm.sre, (2 * lane + n) * 64, rb * 128);
                }
                const int ndep = part < 2 ? 16 : 29;
                const unsigned int epoch = *(volatile unsigned int*)&g_fl.done / gridDim.x + 1;
                const unsigned int* f = part < 2 ? &g_fl.ab[lane & 15] : (lane < 28 ? &g_fl.h[rb * 28 + lane] : &g_fl.y[rb * 2 + n]);
                const unsigned int target = (part < 2 ? 7 : (lane < 27 ? 1 : (lane == 27 ? 2 : 16))) * epoch;
                bool ok = lane >= ndep;
                int published = 0;
                for (int spins = 0; published < ndep && spins < (1 << 22); spins++) {
                    if (!ok) {
                        unsigned int v;
                        asm volatile("ld.acquire.gpu.global.u32 %0, [%1];" : "=r"(v) : "l"(f) : "memory");
                        ok = (int)(v - target) >= 0;
                    }
                    const unsigned int m = __ballot_sync(0xffffffffu, ok);
                    const int cnt = min(__ffs(~m) - 1, ndep);
                    if (m == 0xffffffffu || cnt > published) {
                        published = (m == 0xffffffffu) ? ndep : cnt;
                        fence_async_all();
                        __syncwarp();
                        if (lane == 0) asm volatile("st.release.cta.shared.u32 [%0], %1;" ::"r"(sb + DEP_CNT), "r"(published) : "memory");
                    }
                }
                if (published < ndep && lane == 0)
                    asm volatile("st.release.cta.shared.u32 [%0], %1;" ::"r"(sb + DEP_CNT), "r"(ndep) : "memory");
            }
        } else if (warp == 10) {
            if (lane == 0) {
                for (int p = 0; p < npass; p++) {
                    const int slab = pass_slab(j, p);
                    mbar_wait(sb + BAR_SF, p & 1);
                    if (slab == 27) tma_store(&tm.h64, sb + STG, slab * 64, rb * 128 + n * 64);
                    else if (slab >= 0) tma_store(&tm.h, sb + STG, slab * 64, rb * 128);
                    else tma_store(&tm.abT_st, sb + STG, rb * 128, j * 128);
                    bulk_commit();
                    bulk_wait_read0();
                    asm volatile("st.release.cta.shared.u32 [%0], %1;" ::"r"(sb + SE_CNT), "r"(p + 1) : "memory");
                    bulk_wait0();
                    fence_async_all();
                    if (slab < 0) __threadfence();
                    flag_add(slab >= 0 ? &g_fl.h[rb * 28 + slab] : &g_fl.ab[rb]);
                }
            }
        }
        __syncwarp();
    } else {
        asm volatile("setmaxnreg.inc.sync.aligned.u32 232;");
        const int wg = warp >> 2, wl = warp & 3, wtid = tid & 127;
        const int qd = lane & 3;
        {
            float acc[2][64];
            for (int p = wg; p < npass; p += 2) {
                const int slab = pass_slab(j, p);
                if (p > 0) bar_sync(4 + (p & 1), 256);
                const int handoff = (p + 1 < npass) ? 4 + ((p + 1) & 1) : 0;
                if (slab == 27) s1_mainloop<2>(acc, sb, p, lane, handoff, n);
                else if (slab >= 0) s1_mainloop<1>(acc, sb, p, lane, handoff);
                else s1_mainloop<0>(acc, sb, p, lane, handoff);
                if (p + 2 >= npass && part < 3 && lane == 0) mbar_arrive_both(sb + BAR_S1DONE);
                if (wtid == 0 && p < 4) TL(0, 4 + p);

                const uint32_t srow = sb + STG + (wl * 16 + (lane & 7) + ((lane >> 3) & 1) * 8) * 128;
                if (slab >= 0) {
                    uint32_t hv[2][16];
#pragma unroll
                    for (int mh = 0; mh < 2; mh++) {
                        if (mh == 0 || slab != 27) {
#pragma unroll
                            for (int i = 0; i < 16; i++) {
                                const uint32_t g2 = pack_bf16(acc[mh][2 * i], acc[mh][2 * i + 1]);
                                const uint32_t u2 = pack_bf16(acc[mh][32 + 2 * i], acc[mh][32 + 2 * i + 1]);
                                const uint32_t a2 = pack_bf16(gelu_tanh(bf_lo(g2)), gelu_tanh(bf_hi(g2)));
                                hv[mh][i] = hmul2(a2, u2);
                            }
                        }
                    }
                    cnt_wait(sb + SE_CNT, p);
#pragma unroll
                    for (int mh = 0; mh < 2; mh++) {
                        if (mh == 0 || slab != 27) {
#pragma unroll
                            for (int jj = 0; jj < 8; jj += 2)
                                stmat4(srow + mh * 8192 + (((jj + (lane >> 4)) ^ (lane & 7)) << 4),
                                       hv[mh][2 * jj], hv[mh][2 * jj + 1], hv[mh][2 * jj + 2], hv[mh][2 * jj + 3]);
                        }
                    }
                } else {
#pragma unroll
                    for (int mh = 0; mh < 2; mh++) {
#pragma unroll
                        for (int jj = 0; jj < 8; jj += 2) {
                            const int o = jj * 4;
                            stmat4(srow + mh * 8192 + (((jj + (lane >> 4)) ^ (lane & 7)) << 4),
                                   pack_bf16(acc[mh][o], acc[mh][o + 1]), pack_bf16(acc[mh][o + 2], acc[mh][o + 3]),
                                   pack_bf16(acc[mh][o + 4], acc[mh][o + 5]), pack_bf16(acc[mh][o + 6], acc[mh][o + 7]));
                        }
                    }
                    __nv_bfloat16* dst = g_abT + (size_t)(j * 128 + wl * 16 + (lane >> 2)) * ABP + rb * 128 + 64 + qd * 8;
#pragma unroll
                    for (int mh = 0; mh < 2; mh++) {
#pragma unroll
                        for (int hh = 0; hh < 2; hh++) {
#pragma unroll
                            for (int g4 = 0; g4 < 2; g4++) {
                                uint32_t r[4];
#pragma unroll
                                for (int t = 0; t < 4; t++) {
                                    const int o = 32 + (g4 * 4 + t) * 4 + hh * 2;
                                    r[t] = pack_bf16(acc[mh][o], acc[mh][o + 1]);
                                }
                                quad_transpose(r, qd);
                                __stcg(reinterpret_cast<uint4*>(dst + (size_t)(mh * 64 + hh * 8) * ABP + g4 * 32), make_uint4(r[0], r[1], r[2], r[3]));
                            }
                        }
                    }
                }
                fence_async();
                __syncwarp();
                if (lane == 0) mbar_arrive(sb + BAR_SF);
                if (wtid == 0 && p < 4) TL(0, 10 + p);
            }
        }
        if (wtid == 0) TL(0, 20 + wg);
        if (part < 3) {
            {
                float acc[112];
                const size_t base = (size_t)(rb * 128 + wg * 64 + wl * 16 + (lane >> 2)) * D_ + n * 224 + qd * 8;
                if (part < 2) {
                    s2_mainloop<0>(acc, sb, wg, lane);
                    if (tid == 0) TL(0, 25);
                    uint4* dst = g_y + (size_t)((part * 32 + rb * 2 + n) * 14) * 256 + tid;
#pragma unroll
                    for (int i = 0; i < 14; i++)
                        __stcg(dst + i * 256, make_uint4(pack_bf16(acc[8 * i], acc[8 * i + 1]), pack_bf16(acc[8 * i + 2], acc[8 * i + 3]),
                                                         pack_bf16(acc[8 * i + 4], acc[8 * i + 5]), pack_bf16(acc[8 * i + 6], acc[8 * i + 7])));
                    __threadfence();
                    __syncwarp();
                    if (lane == 0) flag_add(&g_fl.y[rb * 2 + n]);
                } else {
                    uint4 xv[14];
#pragma unroll
                    for (int i = 0; i < 14; i++)
                        xv[i] = __ldg(reinterpret_cast<const uint4*>(pt.x + base + (i / 7) * 8 * D_ + (i % 7) * 32));
                    s2_mainloop<1>(acc, sb, wg, lane);
                    if (tid == 0) TL(0, 25);
                    dep_wait(sb, 29);
                    if (tid == 0) TL(0, 26);
                    const uint4* ysrc = g_y + (size_t)((rb * 2 + n) * 14) * 256 + tid;
                    uint4 yr[14], yi[14];
#pragma unroll
                    for (int i = 0; i < 14; i++) yr[i] = __ldcg(ysrc + i * 256);
                    uint32_t sg[56];
#pragma unroll
                    for (int i = 0; i < 56; i++) {
                        const uint32_t f2 = pack_bf16(acc[2 * i], acc[2 * i + 1]);
                        sg[i] = pack_bf16(silu(bf_lo(f2)), silu(bf_hi(f2)));
                    }
#pragma unroll
                    for (int i = 0; i < 14; i++) yi[i] = __ldcg(ysrc + (32 * 14 + i) * 256);
#pragma unroll
                    for (int i = 0; i < 14; i++) {
                        sg[4 * i + 0] = hmul2(hsub2(yr[i].x, yi[i].x), sg[4 * i + 0]);
                        sg[4 * i + 1] = hmul2(hsub2(yr[i].y, yi[i].y), sg[4 * i + 1]);
                        sg[4 * i + 2] = hmul2(hsub2(yr[i].z, yi[i].z), sg[4 * i + 2]);
                        sg[4 * i + 3] = hmul2(hsub2(yr[i].w, yi[i].w), sg[4 * i + 3]);
                    }
#pragma unroll
                    for (int hh = 0; hh < 2; hh++) {
#pragma unroll
                        for (int g4 = 0; g4 < 7; g4++) {
                            uint32_t r[4];
#pragma unroll
                            for (int t = 0; t < 4; t++) r[t] = sg[(g4 * 4 + t) * 2 + hh];
                            quad_transpose(r, qd);
                            const uint4 xx = xv[hh * 7 + g4];
                            *reinterpret_cast<uint4*>(pt.out + base + hh * 8 * D_ + g4 * 32) =
                                make_uint4(hadd2(xx.x, r[0]), hadd2(xx.y, r[1]), hadd2(xx.z, r[2]), hadd2(xx.w, r[3]));
                        }
                    }
                }
            }
        }
    }
    if (tid == 0) TL(0, 29);
    __syncthreads();
    if (tid == 0) {
        TL(0, 30);
        atomicAdd(&g_fl.done, 1u);
    }
}

typedef CUresult (*EncFn)(CUtensorMap*, CUtensorMapDataType, cuuint32_t, void*, const cuuint64_t*, const cuuint64_t*,
                          const cuuint32_t*, const cuuint32_t*, CUtensorMapInterleave, CUtensorMapSwizzle,
                          CUtensorMapL2promotion, CUtensorMapFloatOOBfill);

void make_map(EncFn enc, CUtensorMap* m, const void* ptr, int rows, int cols, int box_rows, int box_cols, int pitch = 0) {
    const bool swz = true;
    cuuint64_t gd[2] = {(cuuint64_t)cols, (cuuint64_t)rows};
    cuuint64_t gs[1] = {(cuuint64_t)(pitch ? pitch : cols) * 2};
    cuuint32_t bx[2] = {(cuuint32_t)box_cols, (cuuint32_t)box_rows};
    cuuint32_t es[2] = {1, 1};
    enc(m, CU_TENSOR_MAP_DATA_TYPE_BFLOAT16, 2, const_cast<void*>(ptr), gd, gs, bx, es, CU_TENSOR_MAP_INTERLEAVE_NONE,
        swz ? CU_TENSOR_MAP_SWIZZLE_128B : CU_TENSOR_MAP_SWIZZLE_NONE, CU_TENSOR_MAP_L2_PROMOTION_L2_128B,
        CU_TENSOR_MAP_FLOAT_OOB_FILL_NONE);
}

}

extern "C" void kernel_launch(void* const* d_in, const int* in_sizes, int n_in, void* d_out, int out_size) {
    Ptrs pt;
    pt.x = (const __nv_bfloat16*)d_in[0];
    pt.hre = (const __nv_bfloat16*)d_in[3];
    pt.him = (const __nv_bfloat16*)d_in[4];
    pt.wg = (const __nv_bfloat16*)d_in[6];
    pt.wu = (const __nv_bfloat16*)d_in[7];
    pt.wd = (const __nv_bfloat16*)d_in[8];
    pt.out = (__nv_bfloat16*)d_out;

    void* fn = nullptr;
    cudaDriverEntryPointQueryResult qr;
    cudaGetDriverEntryPoint("cuTensorMapEncodeTiled", &fn, cudaEnableDefault, &qr);
    EncFn enc = (EncFn)fn;
    void *p_abT, *p_h;
    cudaGetSymbolAddress(&p_abT, g_abT);
    cudaGetSymbolAddress(&p_h, g_h);

    Maps tm;
    make_map(enc, &tm.wg, d_in[6], D_, F_, 64, 64);
    make_map(enc, &tm.wu, d_in[7], D_, F_, 64, 64);
    make_map(enc, &tm.hre, d_in[3], D_, D_, 64, 64);
    make_map(enc, &tm.him, d_in[4], D_, D_, 64, 64);
    make_map(enc, &tm.h, p_h, S_, F_, 128, 64);
    make_map(enc, &tm.h64, p_h, S_, F_, 64, 64);
    make_map(enc, &tm.abT, p_abT, 896, S_, 112, 64, ABP);
    make_map(enc, &tm.abT_st, p_abT, 896, S_, 128, 64, ABP);
    make_map(enc, &tm.sre, d_in[1], S_, S_, 128, 64);
    make_map(enc, &tm.sim, d_in[2], S_, S_, 128, 64);
    make_map(enc, &tm.wd, d_in[8], F_, D_, 64, 64);

    cudaFuncSetAttribute(fused_kernel, cudaFuncAttributeMaxDynamicSharedMemorySize, SMEM_BYTES);

    cudaLaunchAttribute at[1];
    at[0].id = cudaLaunchAttributeClusterDimension;
    at[0].val.clusterDim.x = 2; at[0].val.clusterDim.y = 1; at[0].val.clusterDim.z = 1;
    cudaLaunchConfig_t cfg = {};
    cfg.gridDim = dim3(128); cfg.blockDim = dim3(384); cfg.stream = cudaStreamPerThread;
    cfg.attrs = at; cfg.numAttrs = 1;
    cfg.dynamicSmemBytes = SMEM_BYTES;
    cudaLaunchKernelEx(&cfg, fused_kernel, pt, tm);
}
```

```cpp
#include <cuda_runtime.h>
#include <cuda_bf16.h>
#include <cuda.h>
#include <stdint.h>

namespace {

constexpr int S_ = 2048, D_ = 448, F_ = 1792;

constexpr int ABP = 2048 + 64;
__device__ __align__(1024) __nv_bfloat16 g_abT[896 * ABP];
__device__ __align__(1024) __nv_bfloat16 g_h[2048 * 1792];
__device__ __align__(1024) uint4 g_y[2 * 32 * 14 * 256];
struct Flags {
    unsigned int ab[16];
    unsigned int h[16 * 28];
    unsigned int y[32];
    unsigned int done;
};
__device__ Flags g_fl;

#define TL(k, i) do {} while (0)
__device__ __forceinline__ uint32_t s2u(const void* p) { return (uint32_t)__cvta_generic_to_shared(p); }
__device__ __forceinline__ void mbar_init(uint32_t b, int c) {
    asm volatile("mbarrier.init.shared::cta.b64 [%0], %1;" ::"r"(b), "r"(c));
}
__device__ __forceinline__ void mbar_expect(uint32_t b, uint32_t bytes) {
    asm volatile("mbarrier.arrive.expect_tx.shared::cta.b64 _, [%0], %1;" ::"r"(b), "r"(bytes) : "memory");
}
__device__ __forceinline__ void mbar_wait(uint32_t b, uint32_t ph) {
    uint32_t ok;
    do {
        asm volatile("{\n.reg .pred p;\nmbarrier.try_wait.parity.shared::cta.b64 p, [%1], %2;\nselp.u32 %0, 1, 0, p;\n}"
                     : "=r"(ok) : "r"(b), "r"(ph) : "memory");
    } while (!ok);
}
__device__ __forceinline__ void mbar_arrive_both(uint32_t b) {
    asm volatile("{\n.reg .b32 r0, r1;\n"
                 "mapa.shared::cluster.u32 r0, %0, 0;\n"
                 "mapa.shared::cluster.u32 r1, %0, 1;\n"
                 "mbarrier.arrive.shared::cluster.b64 _, [r0];\n"
                 "mbarrier.arrive.shared::cluster.b64 _, [r1];\n}"
                 ::"r"(b) : "memory");
}
__device__ __forceinline__ void tma_load(uint32_t dst, const CUtensorMap* m, uint32_t bar, int c0, int c1) {
    asm volatile("cp.async.bulk.tensor.2d.shared::cluster.global.mbarrier::complete_tx::bytes [%0], [%1, {%3, %4}], [%2];"
                 ::"r"(dst), "l"(m), "r"(bar), "r"(c0), "r"(c1) : "memory");
}
__device__ __forceinline__ void tma_load_mc(uint32_t dst, const CUtensorMap* m, uint32_t bar, int c0, int c1) {
    asm volatile("cp.async.bulk.tensor.2d.shared::cluster.global.mbarrier::complete_tx::bytes.multicast::cluster [%0], [%1, {%3, %4}], [%2], %5;"
                 ::"r"(dst), "l"(m), "r"(bar), "r"(c0), "r"(c1), "h"((uint16_t)3) : "memory");
}
__device__ __forceinline__ void tma_store(const CUtensorMap* m, uint32_t src, int c0, int c1) {
    asm volatile("cp.async.bulk.tensor.2d.global.shared::cta.bulk_group [%0, {%2, %3}], [%1];"
                 ::"l"(m), "r"(src), "r"(c0), "r"(c1) : "memory");
}
__device__ __forceinline__ void bulk_commit() { asm volatile("cp.async.bulk.commit_group;" ::: "memory"); }
__device__ __forceinline__ void bulk_wait_read0() { asm volatile("cp.async.bulk.wait_group.read 0;" ::: "memory"); }
__device__ __forceinline__ void bulk_wait0() { asm volatile("cp.async.bulk.wait_group 0;" ::: "memory"); }
__device__ __forceinline__ void fence_async() { asm volatile("fence.proxy.async.shared::cta;" ::: "memory"); }
__device__ __forceinline__ void fence_async_all() { asm volatile("fence.proxy.async;" ::: "memory"); }
__device__ __forceinline__ void cluster_sync() {
    asm volatile("barrier.cluster.arrive.release.aligned;\nbarrier.cluster.wait.acquire.aligned;" ::: "memory");
}
__device__ __forceinline__ void bar_sync(int id, int n) { asm volatile("bar.sync %0, %1;" ::"r"(id), "r"(n) : "memory"); }
__device__ __forceinline__ void wg_arrive() { asm volatile("wgmma.fence.sync.aligned;" ::: "memory"); }
__device__ __forceinline__ void wg_commit() { asm volatile("wgmma.commit_group.sync.aligned;" ::: "memory"); }
template <int N> __device__ __forceinline__ void wg_wait() { asm volatile("wgmma.wait_group.sync.aligned %0;" ::"n"(N) : "memory"); }
__device__ __forceinline__ void stmat4(uint32_t a, uint32_t r0, uint32_t r1, uint32_t r2, uint32_t r3) {
    asm volatile("stmatrix.sync.aligned.m8n8.x4.shared.b16 [%0], {%1, %2, %3, %4};" ::"r"(a), "r"(r0), "r"(r1), "r"(r2), "r"(r3) : "memory");
}
__device__ __forceinline__ void stmat4t(uint32_t a, uint32_t r0, uint32_t r1, uint32_t r2, uint32_t r3) {
    asm volatile("stmatrix.sync.aligned.m8n8.x4.trans.shared.b16 [%0], {%1, %2, %3, %4};" ::"r"(a), "r"(r0), "r"(r1), "r"(r2), "r"(r3) : "memory");
}
__device__ __forceinline__ void ldmat4(uint32_t a, uint32_t (&r)[4]) {
    asm volatile("ldmatrix.sync.aligned.m8n8.x4.shared.b16 {%0, %1, %2, %3}, [%4];"
                 : "=r"(r[0]), "=r"(r[1]), "=r"(r[2]), "=r"(r[3]) : "r"(a) : "memory");
}
__device__ __forceinline__ void flag_add(unsigned int* f) {
    asm volatile("red.release.gpu.global.add.u32 [%0], 1;" ::"l"(f) : "memory");
}
__device__ __forceinline__ void flag_wait(const unsigned int* f, unsigned int target) {
    unsigned int v;
    int spins = 0;
    while (true) {
        asm volatile("ld.acquire.gpu.global.u32 %0, [%1];" : "=r"(v) : "l"(f) : "memory");
        if ((int)(v - target) >= 0 || ++spins > (1 << 22)) break;
    }
}
__device__ __forceinline__ void quad_transpose(uint32_t (&r)[4], int q) {
    const bool o1 = q & 1, o2 = q & 2;
    uint32_t a = o1 ? r[0] : r[1], b = o1 ? r[2] : r[3];
    a = __shfl_xor_sync(0xffffffffu, a, 1);
    b = __shfl_xor_sync(0xffffffffu, b, 1);
    if (o1) { r[0] = a; r[2] = b; } else { r[1] = a; r[3] = b; }
    a = o2 ? r[0] : r[2]; b = o2 ? r[1] : r[3];
    a = __shfl_xor_sync(0xffffffffu, a, 2);
    b = __shfl_xor_sync(0xffffffffu, b, 2);
    if (o2) { r[0] = a; r[1] = b; } else { r[2] = a; r[3] = b; }
}
__device__ __forceinline__ uint32_t movmat_t(uint32_t v) {
    uint32_t r;
    asm volatile("movmatrix.sync.aligned.m8n8.trans.b16 %0, %1;" : "=r"(r) : "r"(v));
    return r;
}
__device__ __forceinline__ uint64_t mkdesc(uint32_t addr, uint32_t lbo, uint32_t sbo) {
    return (uint64_t)((addr & 0x3FFFF) >> 4) | ((uint64_t)(lbo >> 4) << 16) | ((uint64_t)(sbo >> 4) << 32) | (1ull << 62);
}
__device__ __forceinline__ uint32_t pack_bf16(float lo, float hi) {
    uint32_t r;
    asm("cvt.rn.bf16x2.f32 %0, %1, %2;" : "=r"(r) : "f"(hi), "f"(lo));
    return r;
}
__device__ __forceinline__ uint32_t hsub2(uint32_t a, uint32_t b) { uint32_t r; asm("sub.rn.bf16x2 %0, %1, %2;" : "=r"(r) : "r"(a), "r"(b)); return r; }
__device__ __forceinline__ uint32_t hadd2(uint32_t a, uint32_t b) { uint32_t r; asm("add.rn.bf16x2 %0, %1, %2;" : "=r"(r) : "r"(a), "r"(b)); return r; }
__device__ __forceinline__ uint32_t hmul2(uint32_t a, uint32_t b) { uint32_t r; asm("mul.rn.bf16x2 %0, %1, %2;" : "=r"(r) : "r"(a), "r"(b)); return r; }
__device__ __forceinline__ uint32_t hfma2(uint32_t a, uint32_t b, uint32_t c) { uint32_t r; asm("fma.rn.bf16x2 %0, %1, %2, %3;" : "=r"(r) : "r"(a), "r"(b), "r"(c)); return r; }
__device__ __forceinline__ float bf_lo(uint32_t u) { return __uint_as_float(u << 16); }
__device__ __forceinline__ float bf_hi(uint32_t u) { return __uint_as_float(u & 0xffff0000u); }
__device__ __forceinline__ float rbf(float v) { return __bfloat162float(__float2bfloat16_rn(v)); }
__device__ __forceinline__ float tanh_fast(float x) { float r; asm("tanh.approx.f32 %0, %1;" : "=f"(r) : "f"(x)); return r; }
__device__ __forceinline__ float gelu_tanh(float x) {
    float u = x * fmaf(x * x, 0.0356774081f, 0.7978845608f);
    float hx = 0.5f * x;
    return fmaf(hx, tanh_fast(u), hx);
}
__device__ __forceinline__ float silu(float f) { const float hf = 0.5f * f; return fmaf(hf, tanh_fast(hf), hf); }

template <int TB>
__device__ __forceinline__ void wgmma_n128(float (&d)[64], uint64_t da, uint64_t db, int scaleD) {
    asm volatile("{\n.reg .pred p;\nsetp.ne.b32 p, %66, 0;\n"
        "wgmma.mma_async.sync.aligned.m64n128k16.f32.bf16.bf16 {%0, %1, %2, %3, %4, %5, %6, %7, %8, %9, %10, %11, %12, %13, %14, %15, %16, %17, %18, %19, %20, %21, %22, %23, %24, %25, %26, %27, %28, %29, %30, %31, %32, %33, %34, %35, %36, %37, %38, %39, %40, %41, %42, %43, %44, %45, %46, %47, %48, %49, %50, %51, %52, %53, %54, %55, %56, %57, %58, %59, %60, %61, %62, %63}, %64, %65, p, 1, 1, 0, %67;\n}\n"
        : "+f"(d[0]), "+f"(d[1]), "+f"(d[2]), "+f"(d[3]), "+f"(d[4]), "+f"(d[5]), "+f"(d[6]), "+f"(d[7]), "+f"(d[8]), "+f"(d[9]), "+f"(d[10]), "+f"(d[11]), "+f"(d[12]), "+f"(d[13]), "+f"(d[14]), "+f"(d[15]), "+f"(d[16]), "+f"(d[17]), "+f"(d[18]), "+f"(d[19]), "+f"(d[20]), "+f"(d[21]), "+f"(d[22]), "+f"(d[23]), "+f"(d[24]), "+f"(d[25]), "+f"(d[26]), "+f"(d[27]), "+f"(d[28]), "+f"(d[29]), "+f"(d[30]), "+f"(d[31]), "+f"(d[32]), "+f"(d[33]), "+f"(d[34]), "+f"(d[35]), "+f"(d[36]), "+f"(d[37]), "+f"(d[38]), "+f"(d[39]), "+f"(d[40]), "+f"(d[41]), "+f"(d[42]), "+f"(d[43]), "+f"(d[44]), "+f"(d[45]), "+f"(d[46]), "+f"(d[47]), "+f"(d[48]), "+f"(d[49]), "+f"(d[50]), "+f"(d[51]), "+f"(d[52]), "+f"(d[53]), "+f"(d[54]), "+f"(d[55]), "+f"(d[56]), "+f"(d[57]), "+f"(d[58]), "+f"(d[59]), "+f"(d[60]), "+f"(d[61]), "+f"(d[62]), "+f"(d[63])
        : "l"(da), "l"(db), "r"(scaleD), "n"(TB));
}
template <int TB>
__device__ __forceinline__ void wgmma_n224(float (&d)[112], uint64_t da, uint64_t db, int scaleD) {
    asm volatile("{\n.reg .pred p;\nsetp.ne.b32 p, %114, 0;\n"
        "wgmma.mma_async.sync.aligned.m64n224k16.f32.bf16.bf16 {%0, %1, %2, %3, %4, %5, %6, %7, %8, %9, %10, %11, %12, %13, %14, %15, %16, %17, %18, %19, %20, %21, %22, %23, %24, %25, %26, %27, %28, %29, %30, %31, %32, %33, %34, %35, %36, %37, %38, %39, %40, %41, %42, %43, %44, %45, %46, %47, %48, %49, %50, %51, %52, %53, %54, %55, %56, %57, %58, %59, %60, %61, %62, %63, %64, %65, %66, %67, %68, %69, %70, %71, %72, %73, %74, %75, %76, %77, %78, %79, %80, %81, %82, %83, %84, %85, %86, %87, %88, %89, %90, %91, %92, %93, %94, %95, %96, %97, %98, %99, %100, %101, %102, %103, %104, %105, %106, %107, %108, %109, %110, %111}, %112, %113, p, 1, 1, 0, %115;\n}\n"
        : "+f"(d[0]), "+f"(d[1]), "+f"(d[2]), "+f"(d[3]), "+f"(d[4]), "+f"(d[5]), "+f"(d[6]), "+f"(d[7]), "+f"(d[8]), "+f"(d[9]), "+f"(d[10]), "+f"(d[11]), "+f"(d[12]), "+f"(d[13]), "+f"(d[14]), "+f"(d[15]), "+f"(d[16]), "+f"(d[17]), "+f"(d[18]), "+f"(d[19]), "+f"(d[20]), "+f"(d[21]), "+f"(d[22]), "+f"(d[23]), "+f"(d[24]), "+f"(d[25]), "+f"(d[26]), "+f"(d[27]), "+f"(d[28]), "+f"(d[29]), "+f"(d[30]), "+f"(d[31]), "+f"(d[32]), "+f"(d[33]), "+f"(d[34]), "+f"(d[35]), "+f"(d[36]), "+f"(d[37]), "+f"(d[38]), "+f"(d[39]), "+f"(d[40]), "+f"(d[41]), "+f"(d[42]), "+f"(d[43]), "+f"(d[44]), "+f"(d[45]), "+f"(d[46]), "+f"(d[47]), "+f"(d[48]), "+f"(d[49]), "+f"(d[50]), "+f"(d[51]), "+f"(d[52]), "+f"(d[53]), "+f"(d[54]), "+f"(d[55]), "+f"(d[56]), "+f"(d[57]), "+f"(d[58]), "+f"(d[59]), "+f"(d[60]), "+f"(d[61]), "+f"(d[62]), "+f"(d[63]), "+f"(d[64]), "+f"(d[65]), "+f"(d[66]), "+f"(d[67]), "+f"(d[68]), "+f"(d[69]), "+f"(d[70]), "+f"(d[71]), "+f"(d[72]), "+f"(d[73]), "+f"(d[74]), "+f"(d[75]), "+f"(d[76]), "+f"(d[77]), "+f"(d[78]), "+f"(d[79]), "+f"(d[80]), "+f"(d[81]), "+f"(d[82]), "+f"(d[83]), "+f"(d[84]), "+f"(d[85]), "+f"(d[86]), "+f"(d[87]), "+f"(d[88]), "+f"(d[89]), "+f"(d[90]), "+f"(d[91]), "+f"(d[92]), "+f"(d[93]), "+f"(d[94]), "+f"(d[95]), "+f"(d[96]), "+f"(d[97]), "+f"(d[98]), "+f"(d[99]), "+f"(d[100]), "+f"(d[101]), "+f"(d[102]), "+f"(d[103]), "+f"(d[104]), "+f"(d[105]), "+f"(d[106]), "+f"(d[107]), "+f"(d[108]), "+f"(d[109]), "+f"(d[110]), "+f"(d[111])
        : "l"(da), "l"(db), "r"(scaleD), "n"(TB));
}

constexpr int S1_STAGES = 6;
constexpr int S1_XN = 0;
constexpr int S1_B = 7 * 16384;
constexpr int STG = S1_B + S1_STAGES * 16384;
constexpr int Y_STAGES = 4, Y_STAGE = 45056;
constexpr int F_STAGES = 4, F_STAGE = 49152;
constexpr int BAR = STG + 16384;
constexpr int BAR_F1 = BAR, BAR_E1 = BAR + 56, BAR_F2 = BAR + 112, BAR_E2 = BAR + 152, BAR_S1DONE = BAR + 192;
constexpr int BAR_SF = BAR + 208;
constexpr int SE_CNT = BAR + 216;
constexpr int DEP_CNT = BAR + 200;
constexpr int SMEM_BYTES = BAR + 256 + 1024;
constexpr int TPITCH = 464;

__device__ __forceinline__ int n_passes(int j) { return j < 4 ? 2 : (j < 6 ? 4 : 10); }
__device__ __forceinline__ int pass_slab(int j, int p) {
    if (p == 0) return j < 7 ? -1 : 0;
    if (p == 1) return 1 + j;
    if (p < 4) return 4 * p - 3 + j;
    if (p == 9) return 27;
    return 17 + 2 * (p - 4) + (j - 6);
}

template <int TB>
__device__ __forceinline__ void s1_mainloop(float (&acc)[2][64], uint32_t sb, int p, int lane, int handoff, int half = 0) {
    int st = (p * 7) % S1_STAGES;
    uint32_t ph = ((p * 7) / S1_STAGES) & 1;
    int prev = 0;
    uint64_t dx = mkdesc(sb + S1_XN + half * 8192, 16, 1024);
    const uint64_t dw0 = TB ? mkdesc(sb + S1_B, 8192, 1024) : mkdesc(sb + S1_B, 16, 1024);
    const int nrel = lane == 0 ? (handoff ? 7 : 7 - S1_STAGES) : 0;
#pragma unroll 1
    for (int kb = 0; kb < 7; kb++) {
        mbar_wait(sb + BAR_F1 + 8 * st, ph);
        if (kb == 6 && handoff) asm volatile("bar.arrive %0, 256;" ::"r"(handoff) : "memory");
        const uint64_t dw = dw0 + st * 1024;
        wg_arrive();
#pragma unroll
        for (int s = 0; s < 4; s++) {
            if (TB == 2) {
                wgmma_n128<1>(acc[0], dx + s * 2, dw + s * 128, kb | s);
            } else if (TB) {
                wgmma_n128<1>(acc[0], dx + s * 2, dw + s * 128, kb | s);
                wgmma_n128<1>(acc[1], dx + 512 + s * 2, dw + s * 128, kb | s);
            } else {
                wgmma_n128<0>(acc[0], dw + s * 2, dx + s * 2, kb | s);
                wgmma_n128<0>(acc[1], dw + 512 + s * 2, dx + s * 2, kb | s);
            }
        }
        wg_commit();
        wg_wait<1>();
        if (kb > 0 && kb <= nrel) mbar_arrive_both(sb + BAR_E1 + 8 * prev);
        prev = st;
        dx += 1024;
        if (++st == S1_STAGES) { st = 0; ph ^= 1; }
    }
    wg_wait<0>();
    if (TB && nrel == 7) mbar_arrive_both(sb + BAR_E1 + 8 * prev);
}

template <int TB>
__device__ __forceinline__ void s2_mainloop(float (&acc)[112], uint32_t sb, int wg, int lane) {
    constexpr int NST = TB ? F_STAGES : Y_STAGES, SSZ = TB ? F_STAGE : Y_STAGE, NKB = TB ? 28 : 32;
    int st = 0;
    uint32_t ph = 0;
    int prev = 0;
    const uint64_t da0 = mkdesc(sb + wg * 8192, 16, 1024);
    const uint64_t db0 = TB ? mkdesc(sb + 16384, 8192, 1024) : mkdesc(sb + 16384, 16, 1024);
#pragma unroll 1
    for (int i = 0; i < NKB; i++) {
        mbar_wait(sb + BAR_F2 + 8 * st, ph);
        if (threadIdx.x == 0 && (i == 0 || i == 8 || i == 16 || i == 24 || i == 26 || i == 27)) TL(0, 14 + (i == 26 ? 4 : (i == 27 ? 5 : i / 8)));
        const uint64_t da = da0 + st * (SSZ / 16), db = db0 + st * (SSZ / 16);
        wg_arrive();
#pragma unroll
        for (int s = 0; s < 4; s++) wgmma_n224<TB>(acc, da + s * 2, db + s * (TB ? 128 : 2), i | s);
        wg_commit();
        wg_wait<1>();
        if (i > 0 && i <= NKB - NST && lane == 0) mbar_arrive_both(sb + BAR_E2 + 8 * prev);
        prev = st;
        if (++st == NST) { st = 0; ph ^= 1; }
    }
    wg_wait<0>();
}

struct Maps {
    CUtensorMap wg, wu, hre, him, h, h64, abT, abT_st, sre, sim, wd;
};
struct Ptrs {
    const __nv_bfloat16 *x, *hre, *him, *wg, *wu, *wd;
    __nv_bfloat16* out;
};
__device__ __forceinline__ void mbar_arrive(uint32_t b) {
    asm volatile("mbarrier.arrive.shared::cta.b64 _, [%0];" ::"r"(b) : "memory");
}
__device__ __forceinline__ void l2_prefetch(const void* p, uint32_t bytes) {
    asm volatile("cp.async.bulk.prefetch.L2.global [%0], %1;" ::"l"(p), "r"(bytes) : "memory");
}
__device__ __forceinline__ void tma_prefetch(const CUtensorMap* m, int c0, int c1) {
    asm volatile("cp.async.bulk.prefetch.tensor.2d.L2.global.tile [%0, {%1, %2}];" ::"l"(m), "r"(c0), "r"(c1) : "memory");
}

__device__ __forceinline__ void cnt_wait(uint32_t addr, uint32_t need) {
    uint32_t v;
    do { asm volatile("ld.acquire.cta.shared.u32 %0, [%1];" : "=r"(v) : "r"(addr) : "memory"); } while (v < need);
}
__device__ __forceinline__ void dep_wait(uint32_t sb, uint32_t need) { cnt_wait(sb + DEP_CNT, need); }

__global__ void __launch_bounds__(384, 1)
fused_kernel(const __grid_constant__ Ptrs pt, const __grid_constant__ Maps tm) {
    extern __shared__ unsigned char smem_raw[];
    const uint32_t sb = (s2u(smem_raw) + 1023) & ~1023u;
    const int tid = threadIdx.x, lane = tid & 31;
    const int warp = __shfl_sync(0xffffffffu, tid >> 5, 0);
    const int rank = blockIdx.x & 1;
    const int cid = blockIdx.x >> 1;
    const int j = cid & 7;
    const int rb = (cid >> 3) * 2 + rank;
    const int npass = n_passes(j);
    const int n = j & 1;
    const int part = j >> 1;

    {
        const int l8 = lane & 7, sub = lane >> 3;
        uint4 v[3][7];
#pragma unroll
        for (int it = 0; it < 3; it++) {
            const int qd = warp + 12 * it;
            if (qd < 32) {
                const uint4* src = reinterpret_cast<const uint4*>(pt.x + (size_t)(rb * 128 + qd * 4 + sub) * D_) + l8;
#pragma unroll
                for (int i = 0; i < 7; i++) v[it][i] = __ldg(src + i * 8);
            }
        }
        if (tid == 256) {
            TL(0, 0);
            for (int i = 0; i < S1_STAGES; i++) { mbar_init(sb + BAR_F1 + 8 * i, 1); mbar_init(sb + BAR_E1 + 8 * i, 8); }
            for (int i = 0; i < Y_STAGES; i++) { mbar_init(sb + BAR_F2 + 8 * i, 1); mbar_init(sb + BAR_E2 + 8 * i, 16); }
            mbar_init(sb + BAR_S1DONE, 16);
            mbar_init(sb + BAR_SF, 4);
            asm volatile("st.shared.u32 [%0], %1;" ::"r"(sb + SE_CNT), "r"(0) : "memory");
            asm volatile("st.shared.u32 [%0], %1;" ::"r"(sb + DEP_CNT), "r"(0) : "memory");
            asm volatile("fence.mbarrier_init.release.cluster;" ::: "memory");
        }
        __syncwarp();
        asm volatile("barrier.cluster.arrive.relaxed.aligned;\nbarrier.cluster.wait.aligned;" ::: "memory");
        if (tid == 256) {
            const int slab = pass_slab(j, 0);
            for (int kb = 0; kb < S1_STAGES; kb++) {
                const uint32_t dst = sb + S1_B + kb * 16384 + rank * 8192;
                const uint32_t fb = sb + BAR_F1 + 8 * kb;
                mbar_expect(fb, 16384);
                if (slab >= 0) {
                    tma_load_mc(dst, rank ? &tm.wu : &tm.wg, fb, slab * 64, kb * 64);
                } else {
                    const int a = 2 * j + rank;
                    tma_load_mc(dst, a < 7 ? &tm.hre : &tm.him, fb, kb * 64, (a < 7 ? a : a - 7) * 64);
                }
            }
            const int b = blockIdx.x;
            l2_prefetch((const char*)pt.hre + b * 3136, 3136);
            l2_prefetch((const char*)pt.him + b * 3136, 3136);
            l2_prefetch((const char*)pt.wg + b * 12544, 12544);
            l2_prefetch((const char*)pt.wu + b * 12544, 12544);
            l2_prefetch((const char*)pt.wd + b * 12544, 12544);
        }
        __syncwarp();
        if (tid == 0) TL(0, 1);
#pragma unroll
        for (int it = 0; it < 3; it++) {
            const int qd = warp + 12 * it;
            if (qd < 32) {
                const int row = qd * 4 + sub;
                float s0 = 0.f, s1 = 0.f, q0 = 0.f, q1 = 0.f;
#pragma unroll
                for (int i = 0; i < 7; i++) {
                    const uint32_t w[4] = {v[it][i].x, v[it][i].y, v[it][i].z, v[it][i].w};
#pragma unroll
                    for (int c = 0; c < 4; c++) {
                        const float d0 = bf_lo(w[c]), d1 = bf_hi(w[c]);
                        s0 += d0; s1 += d1;
                        q0 = fmaf(d0, d0, q0);
                        q1 = fmaf(d1, d1, q1);
                    }
                }
                float s = s0 + s1, q = q0 + q1;
#pragma unroll
                for (int o = 1; o < 8; o <<= 1) {
                    s += __shfl_xor_sync(0xffffffffu, s, o);
                    q += __shfl_xor_sync(0xffffffffu, q, o);
                }
                if (it == 0 && tid == 0) TL(0, 3);
                const float mean = s * (1.0f / D_);
                const float var = rbf(fmaxf(fmaf(-mean, mean, q * (1.0f / D_)), 0.f));
                const float den = rbf(sqrtf(rbf(var + 1e-5f)));
                const float rinv = 1.0f / den;
                const float rhi = rbf(rinv);
                const uint32_t m2 = pack_bf16(mean, mean), rhi2 = pack_bf16(rhi, rhi), rlo2 = pack_bf16(rinv - rhi, rinv - rhi);
                const uint32_t dst = sb + S1_XN + row * 128 + ((l8 ^ (row & 7)) << 4);
#pragma unroll
                for (int i = 0; i < 7; i++) {
                    const uint32_t w[4] = {v[it][i].x, v[it][i].y, v[it][i].z, v[it][i].w};
                    uint32_t o[4];
#pragma unroll
                    for (int c = 0; c < 4; c++) {
                        const uint32_t xc = hsub2(w[c], m2);
                        o[c] = hfma2(xc, rhi2, hmul2(xc, rlo2));
                    }
                    asm volatile("st.shared.v4.b32 [%0], {%1, %2, %3, %4};" ::"r"(dst + i * 16384), "r"(o[0]), "r"(o[1]), "r"(o[2]), "r"(o[3]) : "memory");
                }
            }
        }
        fence_async();
        __syncthreads();
        if (tid == 0) TL(0, 2);
    }

    if (warp >= 8) {
        asm volatile("setmaxnreg.dec.sync.aligned.u32 40;");
        if (warp == 8) {
            if (lane == 0) {
                int st = 0;
                uint32_t ph = 0;
                for (int p = 0; p < npass; p++) {
                    const int slab = pass_slab(j, p);
                    for (int kb = p ? 0 : S1_STAGES; kb < 7; kb++) {
                        mbar_wait(sb + BAR_E1 + 8 * st, ph);
                        const uint32_t dst = sb + S1_B + st * 16384 + rank * 8192;
                        const uint32_t fb = sb + BAR_F1 + 8 * st;
                        mbar_expect(fb, 16384);
                        if (slab >= 0) {
                            tma_load_mc(dst, rank ? &tm.wu : &tm.wg, fb, slab * 64, kb * 64);
                        } else {
                            const int a = 2 * j + rank;
                            tma_load_mc(dst, a < 7 ? &tm.hre : &tm.him, fb, kb * 64, (a < 7 ? a : a - 7) * 64);
                        }
                        if (++st == S1_STAGES) { st = 0; ph ^= 1; }
                        if (p == 1 && part < 2) {
                            for (int q = kb; q < 16; q += 7) tma_prefetch(part ? &tm.sim : &tm.sre, (2 * q + n) * 64, rb * 128);
                        }
                    }
                }
                if (part < 3) {
                    mbar_wait(sb + BAR_S1DONE, 0);
                    TL(0, 24);
                    st = 0; ph = 1;
                    if (part < 2) {
                        const CUtensorMap* ma = part ? &tm.sim : &tm.sre;
                        for (int g = 0; g < 32; g++) {
                            mbar_wait(sb + BAR_E2 + 8 * st, ph);
                            const uint32_t dst = sb + st * Y_STAGE;
                            const uint32_t fb = sb + BAR_F2 + 8 * st;
                            mbar_expect(fb, Y_STAGE);
                            tma_load(dst, ma, fb, g * 64, rb * 128);
                            dep_wait(sb, (g >> 1) + 1);
                            tma_load_mc(dst + 16384 + rank * 14336, &tm.abT, fb, g * 64, part * 448 + n * 224 + rank * 112);
                            if (++st == Y_STAGES) { st = 0; ph ^= 1; }
                        }
                    } else {
                        for (int g = 0; g < 28; g++) {
                            mbar_wait(sb + BAR_E2 + 8 * st, ph);
                            const uint32_t dst = sb + st * F_STAGE;
                            const uint32_t fb = sb + BAR_F2 + 8 * st;
                            mbar_expect(fb, F_STAGE);
                            tma_load_mc(dst + 16384 + (2 * rank) * 8192, &tm.wd, fb, n * 224 + (2 * rank) * 64, g * 64);
                            tma_load_mc(dst + 16384 + (2 * rank + 1) * 8192, &tm.wd, fb, n * 224 + (2 * rank + 1) * 64, g * 64);
                            dep_wait(sb, g + 1);
                            tma_load(dst, &tm.h, fb, g * 64, rb * 128);
                            if (++st == F_STAGES) { st = 0; ph ^= 1; }
                        }
                    }
                }
            }
        } else if (warp == 9) {
            if (part < 3) {
                const int ndep = part < 2 ? 16 : 29;
                const unsigned int epoch = *(volatile unsigned int*)&g_fl.done / gridDim.x + 1;
                const unsigned int* f = part < 2 ? &g_fl.ab[lane & 15] : (lane < 28 ? &g_fl.h[rb * 28 + lane] : &g_fl.y[rb * 2 + n]);
                const unsigned int target = (part < 2 ? 7 : (lane < 27 ? 1 : (lane == 27 ? 2 : 16))) * epoch;
                bool ok = lane >= ndep;
                int published = 0;
                for (int spins = 0; published < ndep && spins < (1 << 22); spins++) {
                    if (!ok) {
                        unsigned int v;
                        asm volatile("ld.acquire.gpu.global.u32 %0, [%1];" : "=r"(v) : "l"(f) : "memory");
                        ok = (int)(v - target) >= 0;
                    }
                    const unsigned int m = __ballot_sync(0xffffffffu, ok);
                    const int cnt = min(__ffs(~m) - 1, ndep);
                    if (m == 0xffffffffu || cnt > published) {
                        published = (m == 0xffffffffu) ? ndep : cnt;
                        fence_async_all();
                        __syncwarp();
                        if (lane == 0) asm volatile("st.release.cta.shared.u32 [%0], %1;" ::"r"(sb + DEP_CNT), "r"(published) : "memory");
                    }
                }
                if (published < ndep && lane == 0)
                    asm volatile("st.release.cta.shared.u32 [%0], %1;" ::"r"(sb + DEP_CNT), "r"(ndep) : "memory");
            }
        } else if (warp == 10) {
            if (lane == 0) {
                for (int p = 0; p < npass; p++) {
                    const int slab = pass_slab(j, p);
                    mbar_wait(sb + BAR_SF, p & 1);
                    if (slab == 27) tma_store(&tm.h64, sb + STG, slab * 64, rb * 128 + n * 64);
                    else if (slab >= 0) tma_store(&tm.h, sb + STG, slab * 64, rb * 128);
                    else {
                        tma_store(&tm.abT_st, sb + STG, rb * 128, j * 128);
                        tma_store(&tm.abT_st, sb + S1_B, rb * 128 + 64, j * 128);
                    }
                    bulk_commit();
                    bulk_wait_read0();
                    asm volatile("st.release.cta.shared.u32 [%0], %1;" ::"r"(sb + SE_CNT), "r"(p + 1) : "memory");
                    if (slab < 0) {
                        for (int w = 0; w < 4; w++) mbar_arrive_both(sb + BAR_E1);
                    }
                    bulk_wait0();
                    fence_async_all();
                    flag_add(slab >= 0 ? &g_fl.h[rb * 28 + slab] : &g_fl.ab[rb]);
                }
            }
        }
        __syncwarp();
    } else {
        asm volatile("setmaxnreg.inc.sync.aligned.u32 232;");
        const int wg = warp >> 2, wl = warp & 3, wtid = tid & 127;
        const int qd = lane & 3;
        {
            float acc[2][64];
            for (int p = wg; p < npass; p += 2) {
                const int slab = pass_slab(j, p);
                if (p > 0) bar_sync(4 + (p & 1), 256);
                const int handoff = (p + 1 < npass) ? 4 + ((p + 1) & 1) : 0;
                if (slab == 27) s1_mainloop<2>(acc, sb, p, lane, handoff, n);
                else if (slab >= 0) s1_mainloop<1>(acc, sb, p, lane, handoff);
                else s1_mainloop<0>(acc, sb, p, lane, handoff);
                if (p + 2 >= npass && part < 3 && lane == 0) mbar_arrive_both(sb + BAR_S1DONE);
                if (wtid == 0 && p < 4) TL(0, 4 + p);

                const uint32_t srow = sb + STG + (wl * 16 + (lane & 7) + ((lane >> 3) & 1) * 8) * 128;
                if (slab >= 0) {
                    uint32_t hv[2][16];
#pragma unroll
                    for (int mh = 0; mh < 2; mh++) {
                        if (mh == 0 || slab != 27) {
#pragma unroll
                            for (int i = 0; i < 16; i++) {
                                const uint32_t g2 = pack_bf16(acc[mh][2 * i], acc[mh][2 * i + 1]);
                                const uint32_t u2 = pack_bf16(acc[mh][32 + 2 * i], acc[mh][32 + 2 * i + 1]);
                                const uint32_t a2 = pack_bf16(gelu_tanh(bf_lo(g2)), gelu_tanh(bf_hi(g2)));
                                hv[mh][i] = hmul2(a2, u2);
                            }
                        }
                    }
                    cnt_wait(sb + SE_CNT, p);
#pragma unroll
                    for (int mh = 0; mh < 2; mh++) {
                        if (mh == 0 || slab != 27) {
#pragma unroll
                            for (int jj = 0; jj < 8; jj += 2)
                                stmat4(srow + mh * 8192 + (((jj + (lane >> 4)) ^ (lane & 7)) << 4),
                                       hv[mh][2 * jj], hv[mh][2 * jj + 1], hv[mh][2 * jj + 2], hv[mh][2 * jj + 3]);
                        }
                    }
                } else {
                    bar_sync(2, 128);
#pragma unroll
                    for (int hf = 0; hf < 2; hf++) {
#pragma unroll
                        for (int mh = 0; mh < 2; mh++) {
#pragma unroll
                            for (int jj = 0; jj < 8; jj += 2) {
                                const int o = hf * 32 + jj * 4;
                                stmat4(srow - hf * (STG - S1_B) + mh * 8192 + (((jj + (lane >> 4)) ^ (lane & 7)) << 4),
                                       pack_bf16(acc[mh][o], acc[mh][o + 1]), pack_bf16(acc[mh][o + 2], acc[mh][o + 3]),
                                       pack_bf16(acc[mh][o + 4], acc[mh][o + 5]), pack_bf16(acc[mh][o + 6], acc[mh][o + 7]));
                            }
                        }
                    }
                }
                fence_async();
                __syncwarp();
                if (lane == 0) mbar_arrive(sb + BAR_SF);
                if (wtid == 0 && p < 4) TL(0, 10 + p);
            }
        }
        if (wtid == 0) TL(0, 20 + wg);
        if (part < 3) {
            {
                float acc[112];
                const size_t base = (size_t)(rb * 128 + wg * 64 + wl * 16 + (lane >> 2)) * D_ + n * 224 + qd * 8;
                if (part < 2) {
                    s2_mainloop<0>(acc, sb, wg, lane);
                    if (tid == 0) TL(0, 25);
                    uint4* dst = g_y + (size_t)((part * 32 + rb * 2 + n) * 14) * 256 + tid;
#pragma unroll
                    for (int i = 0; i < 14; i++)
                        __stcg(dst + i * 256, make_uint4(pack_bf16(acc[8 * i], acc[8 * i + 1]), pack_bf16(acc[8 * i + 2], acc[8 * i + 3]),
                                                         pack_bf16(acc[8 * i + 4], acc[8 * i + 5]), pack_bf16(acc[8 * i + 6], acc[8 * i + 7])));
                    __threadfence();
                    __syncwarp();
                    if (lane == 0) flag_add(&g_fl.y[rb * 2 + n]);
                } else {
                    uint4 xv[14];
#pragma unroll
                    for (int i = 0; i < 14; i++)
                        xv[i] = __ldg(reinterpret_cast<const uint4*>(pt.x + base + (i / 7) * 8 * D_ + (i % 7) * 32));
                    s2_mainloop<1>(acc, sb, wg, lane);
                    if (tid == 0) TL(0, 25);
                    dep_wait(sb, 29);
                    if (tid == 0) TL(0, 26);
                    const uint4* ysrc = g_y + (size_t)((rb * 2 + n) * 14) * 256 + tid;
                    uint4 yr[14], yi[14];
#pragma unroll
                    for (int i = 0; i < 14; i++) yr[i] = __ldcg(ysrc + i * 256);
                    uint32_t sg[56];
#pragma unroll
                    for (int i = 0; i < 56; i++) {
                        const uint32_t f2 = pack_bf16(acc[2 * i], acc[2 * i + 1]);
                        sg[i] = pack_bf16(silu(bf_lo(f2)), silu(bf_hi(f2)));
                    }
#pragma unroll
                    for (int i = 0; i < 14; i++) yi[i] = __ldcg(ysrc + (32 * 14 + i) * 256);
#pragma unroll
                    for (int i = 0; i < 14; i++) {
                        sg[4 * i + 0] = hmul2(hsub2(yr[i].x, yi[i].x), sg[4 * i + 0]);
                        sg[4 * i + 1] = hmul2(hsub2(yr[i].y, yi[i].y), sg[4 * i + 1]);
                        sg[4 * i + 2] = hmul2(hsub2(yr[i].z, yi[i].z), sg[4 * i + 2]);
                        sg[4 * i + 3] = hmul2(hsub2(yr[i].w, yi[i].w), sg[4 * i + 3]);
                    }
#pragma unroll
                    for (int hh = 0; hh < 2; hh++) {
#pragma unroll
                        for (int g4 = 0; g4 < 7; g4++) {
                            uint32_t r[4];
#pragma unroll
                            for (int t = 0; t < 4; t++) r[t] = sg[(g4 * 4 + t) * 2 + hh];
                            quad_transpose(r, qd);
                            const uint4 xx = xv[hh * 7 + g4];
                            *reinterpret_cast<uint4*>(pt.out + base + hh * 8 * D_ + g4 * 32) =
                                make_uint4(hadd2(xx.x, r[0]), hadd2(xx.y, r[1]), hadd2(xx.z, r[2]), hadd2(xx.w, r[3]));
                        }
                    }
                }
            }
        }
    }
    if (tid == 0) TL(0, 29);
    __syncthreads();
    if (tid == 0) {
        TL(0, 30);
        atomicAdd(&g_fl.done, 1u);
    }
}

typedef CUresult (*EncFn)(CUtensorMap*, CUtensorMapDataType, cuuint32_t, void*, const cuuint64_t*, const cuuint64_t*,
                          const cuuint32_t*, const cuuint32_t*, CUtensorMapInterleave, CUtensorMapSwizzle,
                          CUtensorMapL2promotion, CUtensorMapFloatOOBfill);

void make_map(EncFn enc, CUtensorMap* m, const void* ptr, int rows, int cols, int box_rows, int box_cols, int pitch = 0) {
    const bool swz = true;
    cuuint64_t gd[2] = {(cuuint64_t)cols, (cuuint64_t)rows};
    cuuint64_t gs[1] = {(cuuint64_t)(pitch ? pitch : cols) * 2};
    cuuint32_t bx[2] = {(cuuint32_t)box_cols, (cuuint32_t)box_rows};
    cuuint32_t es[2] = {1, 1};
    enc(m, CU_TENSOR_MAP_DATA_TYPE_BFLOAT16, 2, const_cast<void*>(ptr), gd, gs, bx, es, CU_TENSOR_MAP_INTERLEAVE_NONE,
        swz ? CU_TENSOR_MAP_SWIZZLE_128B : CU_TENSOR_MAP_SWIZZLE_NONE, CU_TENSOR_MAP_L2_PROMOTION_L2_128B,
        CU_TENSOR_MAP_FLOAT_OOB_FILL_NONE);
}

}

extern "C" void kernel_launch(void* const* d_in, const int* in_sizes, int n_in, void* d_out, int out_size) {
    Ptrs pt;
    pt.x = (const __nv_bfloat16*)d_in[0];
    pt.hre = (const __nv_bfloat16*)d_in[3];
    pt.him = (const __nv_bfloat16*)d_in[4];
    pt.wg = (const __nv_bfloat16*)d_in[6];
    pt.wu = (const __nv_bfloat16*)d_in[7];
    pt.wd = (const __nv_bfloat16*)d_in[8];
    pt.out = (__nv_bfloat16*)d_out;

    void* fn = nullptr;
    cudaDriverEntryPointQueryResult qr;
    cudaGetDriverEntryPoint("cuTensorMapEncodeTiled", &fn, cudaEnableDefault, &qr);
    EncFn enc = (EncFn)fn;
    void *p_abT, *p_h;
    cudaGetSymbolAddress(&p_abT, g_abT);
    cudaGetSymbolAddress(&p_h, g_h);

    Maps tm;
    make_map(enc, &tm.wg, d_in[6], D_, F_, 64, 64);
    make_map(enc, &tm.wu, d_in[7], D_, F_, 64, 64);
    make_map(enc, &tm.hre, d_in[3], D_, D_, 64, 64);
    make_map(enc, &tm.him, d_in[4], D_, D_, 64, 64);
    make_map(enc, &tm.h, p_h, S_, F_, 128, 64);
    make_map(enc, &tm.h64, p_h, S_, F_, 64, 64);
    make_map(enc, &tm.abT, p_abT, 896, S_, 112, 64, ABP);
    make_map(enc, &tm.abT_st, p_abT, 896, S_, 128, 64, ABP);
    make_map(enc, &tm.sre, d_in[1], S_, S_, 128, 64);
    make_map(enc, &tm.sim, d_in[2], S_, S_, 128, 64);
    make_map(enc, &tm.wd, d_in[8], F_, D_, 64, 64);

    cudaFuncSetAttribute(fused_kernel, cudaFuncAttributeMaxDynamicSharedMemorySize, SMEM_BYTES);

    cudaLaunchAttribute at[1];
    at[0].id = cudaLaunchAttributeClusterDimension;
    at[0].val.clusterDim.x = 2; at[0].val.clusterDim.y = 1; at[0].val.clusterDim.z = 1;
    cudaLaunchConfig_t cfg = {};
    cfg.gridDim = dim3(128); cfg.blockDim = dim3(384); cfg.stream = cudaStreamPerThread;
    cfg.attrs = at; cfg.numAttrs = 1;
    cfg.dynamicSmemBytes = SMEM_BYTES;
    cudaLaunchKernelEx(&cfg, fused_kernel, pt, tm);
}
```

```cpp
#include <cuda_runtime.h>
#include <cuda_bf16.h>
#include <cuda.h>
#include <stdint.h>

namespace {

constexpr int S_ = 2048, D_ = 448, F_ = 1792;

constexpr int ABP = 2048 + 64;
__device__ __align__(1024) __nv_bfloat16 g_abT[896 * ABP];
__device__ __align__(1024) __nv_bfloat16 g_h[2048 * 1792];
__device__ __align__(1024) uint4 g_y[2 * 32 * 14 * 256];
struct Flags {
    unsigned int ab[16];
    unsigned int h[16 * 28];
    unsigned int y[32];
    unsigned int done;
};
__device__ Flags g_fl;

#define TL(k, i) do {} while (0)
__device__ __forceinline__ uint32_t s2u(const void* p) { return (uint32_t)__cvta_generic_to_shared(p); }
__device__ __forceinline__ void mbar_init(uint32_t b, int c) {
    asm volatile("mbarrier.init.shared::cta.b64 [%0], %1;" ::"r"(b), "r"(c));
}
__device__ __forceinline__ void mbar_expect(uint32_t b, uint32_t bytes) {
    asm volatile("mbarrier.arrive.expect_tx.shared::cta.b64 _, [%0], %1;" ::"r"(b), "r"(bytes) : "memory");
}
__device__ __forceinline__ void mbar_wait(uint32_t b, uint32_t ph) {
    uint32_t ok;
    do {
        asm volatile("{\n.reg .pred p;\nmbarrier.try_wait.parity.shared::cta.b64 p, [%1], %2;\nselp.u32 %0, 1, 0, p;\n}"
                     : "=r"(ok) : "r"(b), "r"(ph) : "memory");
    } while (!ok);
}
__device__ __forceinline__ void mbar_arrive_both(uint32_t b) {
    asm volatile("{\n.reg .b32 r0, r1;\n"
                 "mapa.shared::cluster.u32 r0, %0, 0;\n"
                 "mapa.shared::cluster.u32 r1, %0, 1;\n"
                 "mbarrier.arrive.shared::cluster.b64 _, [r0];\n"
                 "mbarrier.arrive.shared::cluster.b64 _, [r1];\n}"
                 ::"r"(b) : "memory");
}
__device__ __forceinline__ void tma_load(uint32_t dst, const CUtensorMap* m, uint32_t bar, int c0, int c1) {
    asm volatile("cp.async.bulk.tensor.2d.shared::cluster.global.mbarrier::complete_tx::bytes [%0], [%1, {%3, %4}], [%2];"
                 ::"r"(dst), "l"(m), "r"(bar), "r"(c0), "r"(c1) : "memory");
}
__device__ __forceinline__ void tma_load_mc(uint32_t dst, const CUtensorMap* m, uint32_t bar, int c0, int c1) {
    asm volatile("cp.async.bulk.tensor.2d.shared::cluster.global.mbarrier::complete_tx::bytes.multicast::cluster [%0], [%1, {%3, %4}], [%2], %5;"
                 ::"r"(dst), "l"(m), "r"(bar), "r"(c0), "r"(c1), "h"((uint16_t)3) : "memory");
}
__device__ __forceinline__ void tma_store(const CUtensorMap* m, uint32_t src, int c0, int c1) {
    asm volatile("cp.async.bulk.tensor.2d.global.shared::cta.bulk_group [%0, {%2, %3}], [%1];"
                 ::"l"(m), "r"(src), "r"(c0), "r"(c1) : "memory");
}
__device__ __forceinline__ void bulk_commit() { asm volatile("cp.async.bulk.commit_group;" ::: "memory"); }
__device__ __forceinline__ void bulk_wait_read0() { asm volatile("cp.async.bulk.wait_group.read 0;" ::: "memory"); }
__device__ __forceinline__ void bulk_wait0() { asm volatile("cp.async.bulk.wait_group 0;" ::: "memory"); }
__device__ __forceinline__ void fence_async() { asm volatile("fence.proxy.async.shared::cta;" ::: "memory"); }
__device__ __forceinline__ void fence_async_all() { asm volatile("fence.proxy.async;" ::: "memory"); }
__device__ __forceinline__ void cluster_sync() {
    asm volatile("barrier.cluster.arrive.release.aligned;\nbarrier.cluster.wait.acquire.aligned;" ::: "memory");
}
__device__ __forceinline__ void bar_sync(int id, int n) { asm volatile("bar.sync %0, %1;" ::"r"(id), "r"(n) : "memory"); }
__device__ __forceinline__ void wg_arrive() { asm volatile("wgmma.fence.sync.aligned;" ::: "memory"); }
__device__ __forceinline__ void wg_commit() { asm volatile("wgmma.commit_group.sync.aligned;" ::: "memory"); }
template <int N> __device__ __forceinline__ void wg_wait() { asm volatile("wgmma.wait_group.sync.aligned %0;" ::"n"(N) : "memory"); }
__device__ __forceinline__ void stmat4(uint32_t a, uint32_t r0, uint32_t r1, uint32_t r2, uint32_t r3) {
    asm volatile("stmatrix.sync.aligned.m8n8.x4.shared.b16 [%0], {%1, %2, %3, %4};" ::"r"(a), "r"(r0), "r"(r1), "r"(r2), "r"(r3) : "memory");
}
__device__ __forceinline__ void stmat4t(uint32_t a, uint32_t r0, uint32_t r1, uint32_t r2, uint32_t r3) {
    asm volatile("stmatrix.sync.aligned.m8n8.x4.trans.shared.b16 [%0], {%1, %2, %3, %4};" ::"r"(a), "r"(r0), "r"(r1), "r"(r2), "r"(r3) : "memory");
}
__device__ __forceinline__ void ldmat4(uint32_t a, uint32_t (&r)[4]) {
    asm volatile("ldmatrix.sync.aligned.m8n8.x4.shared.b16 {%0, %1, %2, %3}, [%4];"
                 : "=r"(r[0]), "=r"(r[1]), "=r"(r[2]), "=r"(r[3]) : "r"(a) : "memory");
}
__device__ __forceinline__ void flag_add(unsigned int* f) {
    asm volatile("red.release.gpu.global.add.u32 [%0], 1;" ::"l"(f) : "memory");
}
__device__ __forceinline__ void flag_wait(const unsigned int* f, unsigned int target) {
    unsigned int v;
    int spins = 0;
    while (true) {
        asm volatile("ld.acquire.gpu.global.u32 %0, [%1];" : "=r"(v) : "l"(f) : "memory");
        if ((int)(v - target) >= 0 || ++spins > (1 << 22)) break;
    }
}
__device__ __forceinline__ void quad_transpose(uint32_t (&r)[4], int q) {
    const bool o1 = q & 1, o2 = q & 2;
    uint32_t a = o1 ? r[0] : r[1], b = o1 ? r[2] : r[3];
    a = __shfl_xor_sync(0xffffffffu, a, 1);
    b = __shfl_xor_sync(0xffffffffu, b, 1);
    if (o1) { r[0] = a; r[2] = b; } else { r[1] = a; r[3] = b; }
    a = o2 ? r[0] : r[2]; b = o2 ? r[1] : r[3];
    a = __shfl_xor_sync(0xffffffffu, a, 2);
    b = __shfl_xor_sync(0xffffffffu, b, 2);
    if (o2) { r[0] = a; r[1] = b; } else { r[2] = a; r[3] = b; }
}
__device__ __forceinline__ uint32_t movmat_t(uint32_t v) {
    uint32_t r;
    asm volatile("movmatrix.sync.aligned.m8n8.trans.b16 %0, %1;" : "=r"(r) : "r"(v));
    return r;
}
__device__ __forceinline__ uint64_t mkdesc(uint32_t addr, uint32_t lbo, uint32_t sbo) {
    return (uint64_t)((addr & 0x3FFFF) >> 4) | ((uint64_t)(lbo >> 4) << 16) | ((uint64_t)(sbo >> 4) << 32) | (1ull << 62);
}
__device__ __forceinline__ uint32_t pack_bf16(float lo, float hi) {
    uint32_t r;
    asm("cvt.rn.bf16x2.f32 %0, %1, %2;" : "=r"(r) : "f"(hi), "f"(lo));
    return r;
}
__device__ __forceinline__ uint32_t hsub2(uint32_t a, uint32_t b) { uint32_t r; asm("sub.rn.bf16x2 %0, %1, %2;" : "=r"(r) : "r"(a), "r"(b)); return r; }
__device__ __forceinline__ uint32_t hadd2(uint32_t a, uint32_t b) { uint32_t r; asm("add.rn.bf16x2 %0, %1, %2;" : "=r"(r) : "r"(a), "r"(b)); return r; }
__device__ __forceinline__ uint32_t hmul2(uint32_t a, uint32_t b) { uint32_t r; asm("mul.rn.bf16x2 %0, %1, %2;" : "=r"(r) : "r"(a), "r"(b)); return r; }
__device__ __forceinline__ uint32_t hfma2(uint32_t a, uint32_t b, uint32_t c) { uint32_t r; asm("fma.rn.bf16x2 %0, %1, %2, %3;" : "=r"(r) : "r"(a), "r"(b), "r"(c)); return r; }
__device__ __forceinline__ float bf_lo(uint32_t u) { return __uint_as_float(u << 16); }
__device__ __forceinline__ float bf_hi(uint32_t u) { return __uint_as_float(u & 0xffff0000u); }
__device__ __forceinline__ float rbf(float v) { return __bfloat162float(__float2bfloat16_rn(v)); }
__device__ __forceinline__ float tanh_fast(float x) { float r; asm("tanh.approx.f32 %0, %1;" : "=f"(r) : "f"(x)); return r; }
__device__ __forceinline__ float gelu_tanh(float x) {
    float u = x * fmaf(x * x, 0.0356774081f, 0.7978845608f);
    float hx = 0.5f * x;
    return fmaf(hx, tanh_fast(u), hx);
}
__device__ __forceinline__ float silu(float f) { const float hf = 0.5f * f; return fmaf(hf, tanh_fast(hf), hf); }

template <int TB>
__device__ __forceinline__ void wgmma_n128(float (&d)[64], uint64_t da, uint64_t db, int scaleD) {
    asm volatile("{\n.reg .pred p;\nsetp.ne.b32 p, %66, 0;\n"
        "wgmma.mma_async.sync.aligned.m64n128k16.f32.bf16.bf16 {%0, %1, %2, %3, %4, %5, %6, %7, %8, %9, %10, %11, %12, %13, %14, %15, %16, %17, %18, %19, %20, %21, %22, %23, %24, %25, %26, %27, %28, %29, %30, %31, %32, %33, %34, %35, %36, %37, %38, %39, %40, %41, %42, %43, %44, %45, %46, %47, %48, %49, %50, %51, %52, %53, %54, %55, %56, %57, %58, %59, %60, %61, %62, %63}, %64, %65, p, 1, 1, 0, %67;\n}\n"
        : "+f"(d[0]), "+f"(d[1]), "+f"(d[2]), "+f"(d[3]), "+f"(d[4]), "+f"(d[5]), "+f"(d[6]), "+f"(d[7]), "+f"(d[8]), "+f"(d[9]), "+f"(d[10]), "+f"(d[11]), "+f"(d[12]), "+f"(d[13]), "+f"(d[14]), "+f"(d[15]), "+f"(d[16]), "+f"(d[17]), "+f"(d[18]), "+f"(d[19]), "+f"(d[20]), "+f"(d[21]), "+f"(d[22]), "+f"(d[23]), "+f"(d[24]), "+f"(d[25]), "+f"(d[26]), "+f"(d[27]), "+f"(d[28]), "+f"(d[29]), "+f"(d[30]), "+f"(d[31]), "+f"(d[32]), "+f"(d[33]), "+f"(d[34]), "+f"(d[35]), "+f"(d[36]), "+f"(d[37]), "+f"(d[38]), "+f"(d[39]), "+f"(d[40]), "+f"(d[41]), "+f"(d[42]), "+f"(d[43]), "+f"(d[44]), "+f"(d[45]), "+f"(d[46]), "+f"(d[47]), "+f"(d[48]), "+f"(d[49]), "+f"(d[50]), "+f"(d[51]), "+f"(d[52]), "+f"(d[53]), "+f"(d[54]), "+f"(d[55]), "+f"(d[56]), "+f"(d[57]), "+f"(d[58]), "+f"(d[59]), "+f"(d[60]), "+f"(d[61]), "+f"(d[62]), "+f"(d[63])
        : "l"(da), "l"(db), "r"(scaleD), "n"(TB));
}
template <int TB>
__device__ __forceinline__ void wgmma_n224(float (&d)[112], uint64_t da, uint64_t db, int scaleD) {
    asm volatile("{\n.reg .pred p;\nsetp.ne.b32 p, %114, 0;\n"
        "wgmma.mma_async.sync.aligned.m64n224k16.f32.bf16.bf16 {%0, %1, %2, %3, %4, %5, %6, %7, %8, %9, %10, %11, %12, %13, %14, %15, %16, %17, %18, %19, %20, %21, %22, %23, %24, %25, %26, %27, %28, %29, %30, %31, %32, %33, %34, %35, %36, %37, %38, %39, %40, %41, %42, %43, %44, %45, %46, %47, %48, %49, %50, %51, %52, %53, %54, %55, %56, %57, %58, %59, %60, %61, %62, %63, %64, %65, %66, %67, %68, %69, %70, %71, %72, %73, %74, %75, %76, %77, %78, %79, %80, %81, %82, %83, %84, %85, %86, %87, %88, %89, %90, %91, %92, %93, %94, %95, %96, %97, %98, %99, %100, %101, %102, %103, %104, %105, %106, %107, %108, %109, %110, %111}, %112, %113, p, 1, 1, 0, %115;\n}\n"
        : "+f"(d[0]), "+f"(d[1]), "+f"(d[2]), "+f"(d[3]), "+f"(d[4]), "+f"(d[5]), "+f"(d[6]), "+f"(d[7]), "+f"(d[8]), "+f"(d[9]), "+f"(d[10]), "+f"(d[11]), "+f"(d[12]), "+f"(d[13]), "+f"(d[14]), "+f"(d[15]), "+f"(d[16]), "+f"(d[17]), "+f"(d[18]), "+f"(d[19]), "+f"(d[20]), "+f"(d[21]), "+f"(d[22]), "+f"(d[23]), "+f"(d[24]), "+f"(d[25]), "+f"(d[26]), "+f"(d[27]), "+f"(d[28]), "+f"(d[29]), "+f"(d[30]), "+f"(d[31]), "+f"(d[32]), "+f"(d[33]), "+f"(d[34]), "+f"(d[35]), "+f"(d[36]), "+f"(d[37]), "+f"(d[38]), "+f"(d[39]), "+f"(d[40]), "+f"(d[41]), "+f"(d[42]), "+f"(d[43]), "+f"(d[44]), "+f"(d[45]), "+f"(d[46]), "+f"(d[47]), "+f"(d[48]), "+f"(d[49]), "+f"(d[50]), "+f"(d[51]), "+f"(d[52]), "+f"(d[53]), "+f"(d[54]), "+f"(d[55]), "+f"(d[56]), "+f"(d[57]), "+f"(d[58]), "+f"(d[59]), "+f"(d[60]), "+f"(d[61]), "+f"(d[62]), "+f"(d[63]), "+f"(d[64]), "+f"(d[65]), "+f"(d[66]), "+f"(d[67]), "+f"(d[68]), "+f"(d[69]), "+f"(d[70]), "+f"(d[71]), "+f"(d[72]), "+f"(d[73]), "+f"(d[74]), "+f"(d[75]), "+f"(d[76]), "+f"(d[77]), "+f"(d[78]), "+f"(d[79]), "+f"(d[80]), "+f"(d[81]), "+f"(d[82]), "+f"(d[83]), "+f"(d[84]), "+f"(d[85]), "+f"(d[86]), "+f"(d[87]), "+f"(d[88]), "+f"(d[89]), "+f"(d[90]), "+f"(d[91]), "+f"(d[92]), "+f"(d[93]), "+f"(d[94]), "+f"(d[95]), "+f"(d[96]), "+f"(d[97]), "+f"(d[98]), "+f"(d[99]), "+f"(d[100]), "+f"(d[101]), "+f"(d[102]), "+f"(d[103]), "+f"(d[104]), "+f"(d[105]), "+f"(d[106]), "+f"(d[107]), "+f"(d[108]), "+f"(d[109]), "+f"(d[110]), "+f"(d[111])
        : "l"(da), "l"(db), "r"(scaleD), "n"(TB));
}

constexpr int S1_STAGES = 6;
constexpr int S1_XN = 0;
constexpr int S1_B = 7 * 16384;
constexpr int STG = S1_B + S1_STAGES * 16384;
constexpr int Y_STAGES = 4, Y_STAGE = 45056;
constexpr int F_STAGES = 4, F_STAGE = 49152;
constexpr int BAR = STG + 16384;
constexpr int BAR_F1 = BAR, BAR_E1 = BAR + 56, BAR_F2 = BAR + 112, BAR_E2 = BAR + 152, BAR_S1DONE = BAR + 192;
constexpr int BAR_SF = BAR + 208;
constexpr int SE_CNT = BAR + 216;
constexpr int DEP_CNT = BAR + 200;
constexpr int SMEM_BYTES = BAR + 256 + 1024;
constexpr int TPITCH = 464;

__device__ __forceinline__ int n_passes(int j) { return j < 4 ? 2 : (j < 6 ? 4 : 10); }
__device__ __forceinline__ int pass_slab(int j, int p) {
    if (p == 0) return j < 7 ? -1 : 0;
    if (p == 1) return 1 + j;
    if (p < 4) return 4 * p - 3 + j;
    if (p == 9) return 27;
    return 17 + 2 * (p - 4) + (j - 6);
}

template <int TB>
__device__ __forceinline__ void s1_mainloop(float (&acc)[2][64], uint32_t sb, int p, int lane, int handoff, int half = 0) {
    int st = (p * 7) % S1_STAGES;
    uint32_t ph = ((p * 7) / S1_STAGES) & 1;
    int prev = 0;
    uint64_t dx = mkdesc(sb + S1_XN + half * 8192, 16, 1024);
    const uint64_t dw0 = TB ? mkdesc(sb + S1_B, 8192, 1024) : mkdesc(sb + S1_B, 16, 1024);
    const int nrel = lane == 0 ? (handoff ? 7 : 7 - S1_STAGES) : 0;
#pragma unroll 1
    for (int kb = 0; kb < 7; kb++) {
        mbar_wait(sb + BAR_F1 + 8 * st, ph);
        if (kb == 6 && handoff) asm volatile("bar.arrive %0, 256;" ::"r"(handoff) : "memory");
        const uint64_t dw = dw0 + st * 1024;
        wg_arrive();
#pragma unroll
        for (int s = 0; s < 4; s++) {
            if (TB == 2) {
                wgmma_n128<1>(acc[0], dx + s * 2, dw + s * 128, kb | s);
            } else if (TB) {
                wgmma_n128<1>(acc[0], dx + s * 2, dw + s * 128, kb | s);
                wgmma_n128<1>(acc[1], dx + 512 + s * 2, dw + s * 128, kb | s);
            } else {
                wgmma_n128<0>(acc[0], dw + s * 2, dx + s * 2, kb | s);
                wgmma_n128<0>(acc[1], dw + 512 + s * 2, dx + s * 2, kb | s);
            }
        }
        wg_commit();
        wg_wait<1>();
        if (kb > 0 && kb <= nrel) mbar_arrive_both(sb + BAR_E1 + 8 * prev);
        prev = st;
        dx += 1024;
        if (++st == S1_STAGES) { st = 0; ph ^= 1; }
    }
    wg_wait<0>();
    if (nrel == 7) mbar_arrive_both(sb + BAR_E1 + 8 * prev);
}

template <int TB>
__device__ __forceinline__ void s2_mainloop(float (&acc)[112], uint32_t sb, int wg, int lane) {
    constexpr int NST = TB ? F_STAGES : Y_STAGES, SSZ = TB ? F_STAGE : Y_STAGE, NKB = TB ? 28 : 32;
    int st = 0;
    uint32_t ph = 0;
    int prev = 0;
    const uint64_t da0 = mkdesc(sb + wg * 8192, 16, 1024);
    const uint64_t db0 = TB ? mkdesc(sb + 16384, 8192, 1024) : mkdesc(sb + 16384, 16, 1024);
#pragma unroll 1
    for (int i = 0; i < NKB; i++) {
        mbar_wait(sb + BAR_F2 + 8 * st, ph);
        if (threadIdx.x == 0 && (i == 0 || i == 8 || i == 16 || i == 24 || i == 26 || i == 27)) TL(0, 14 + (i == 26 ? 4 : (i == 27 ? 5 : i / 8)));
        const uint64_t da = da0 + st * (SSZ / 16), db = db0 + st * (SSZ / 16);
        wg_arrive();
#pragma unroll
        for (int s = 0; s < 4; s++) wgmma_n224<TB>(acc, da + s * 2, db + s * (TB ? 128 : 2), i | s);
        wg_commit();
        wg_wait<1>();
        if (i > 0 && i <= NKB - NST && lane == 0) mbar_arrive_both(sb + BAR_E2 + 8 * prev);
        prev = st;
        if (++st == NST) { st = 0; ph ^= 1; }
    }
    wg_wait<0>();
}

struct Maps {
    CUtensorMap wg, wu, hre, him, h, h64, abT, abT_st, sre, sim, wd;
};
struct Ptrs {
    const __nv_bfloat16 *x, *hre, *him, *wg, *wu, *wd;
    __nv_bfloat16* out;
};
__device__ __forceinline__ void mbar_arrive(uint32_t b) {
    asm volatile("mbarrier.arrive.shared::cta.b64 _, [%0];" ::"r"(b) : "memory");
}
__device__ __forceinline__ void l2_prefetch(const void* p, uint32_t bytes) {
    asm volatile("cp.async.bulk.prefetch.L2.global [%0], %1;" ::"l"(p), "r"(bytes) : "memory");
}
__device__ __forceinline__ void tma_prefetch(const CUtensorMap* m, int c0, int c1) {
    asm volatile("cp.async.bulk.prefetch.tensor.2d.L2.global.tile [%0, {%1, %2}];" ::"l"(m), "r"(c0), "r"(c1) : "memory");
}

__device__ __forceinline__ void cnt_wait(uint32_t addr, uint32_t need) {
    uint32_t v;
    do { asm volatile("ld.acquire.cta.shared.u32 %0, [%1];" : "=r"(v) : "r"(addr) : "memory"); } while (v < need);
}
__device__ __forceinline__ void dep_wait(uint32_t sb, uint32_t need) { cnt_wait(sb + DEP_CNT, need); }

__global__ void __launch_bounds__(384, 1)
fused_kernel(const __grid_constant__ Ptrs pt, const __grid_constant__ Maps tm) {
    extern __shared__ unsigned char smem_raw[];
    const uint32_t sb = (s2u(smem_raw) + 1023) & ~1023u;
    const int tid = threadIdx.x, lane = tid & 31;
    const int warp = __shfl_sync(0xffffffffu, tid >> 5, 0);
    const int rank = blockIdx.x & 1;
    const int cid = blockIdx.x >> 1;
    const int j = cid & 7;
    const int rb = (cid >> 3) * 2 + rank;
    const int npass = n_passes(j);
    const int n = j & 1;
    const int part = j >> 1;

    {
        const int l8 = lane & 7, sub = lane >> 3;
        uint4 v[3][7];
#pragma unroll
        for (int it = 0; it < 3; it++) {
            const int qd = warp + 12 * it;
            if (qd < 32) {
                const uint4* src = reinterpret_cast<const uint4*>(pt.x + (size_t)(rb * 128 + qd * 4 + sub) * D_) + l8;
#pragma unroll
                for (int i = 0; i < 7; i++) v[it][i] = __ldg(src + i * 8);
            }
        }
        if (tid == 256) {
            TL(0, 0);
            for (int i = 0; i < S1_STAGES; i++) { mbar_init(sb + BAR_F1 + 8 * i, 1); mbar_init(sb + BAR_E1 + 8 * i, 8); }
            for (int i = 0; i < Y_STAGES; i++) { mbar_init(sb + BAR_F2 + 8 * i, 1); mbar_init(sb + BAR_E2 + 8 * i, 16); }
            mbar_init(sb + BAR_S1DONE, 16);
            mbar_init(sb + BAR_SF, 4);
            asm volatile("st.shared.u32 [%0], %1;" ::"r"(sb + SE_CNT), "r"(0) : "memory");
            asm volatile("st.shared.u32 [%0], %1;" ::"r"(sb + DEP_CNT), "r"(0) : "memory");
            asm volatile("fence.mbarrier_init.release.cluster;" ::: "memory");
        }
        __syncwarp();
        asm volatile("barrier.cluster.arrive.relaxed.aligned;\nbarrier.cluster.wait.aligned;" ::: "memory");
        if (tid == 256) {
            const int slab = pass_slab(j, 0);
            for (int kb = 0; kb < S1_STAGES; kb++) {
                const uint32_t dst = sb + S1_B + kb * 16384 + rank * 8192;
                const uint32_t fb = sb + BAR_F1 + 8 * kb;
                mbar_expect(fb, 16384);
                if (slab >= 0) {
                    tma_load_mc(dst, rank ? &tm.wu : &tm.wg, fb, slab * 64, kb * 64);
                } else {
                    const int a = 2 * j + rank;
                    tma_load_mc(dst, a < 7 ? &tm.hre : &tm.him, fb, kb * 64, (a < 7 ? a : a - 7) * 64);
                }
            }
            const int b = blockIdx.x;
            l2_prefetch((const char*)pt.hre + b * 3136, 3136);
            l2_prefetch((const char*)pt.him + b * 3136, 3136);
            l2_prefetch((const char*)pt.wg + b * 12544, 12544);
            l2_prefetch((const char*)pt.wu + b * 12544, 12544);
            l2_prefetch((const char*)pt.wd + b * 12544, 12544);
        }
        __syncwarp();
        if (tid == 0) TL(0, 1);
#pragma unroll
        for (int it = 0; it < 3; it++) {
            const int qd = warp + 12 * it;
            if (qd < 32) {
                const int row = qd * 4 + sub;
                float s0 = 0.f, s1 = 0.f, q0 = 0.f, q1 = 0.f;
#pragma unroll
                for (int i = 0; i < 7; i++) {
                    const uint32_t w[4] = {v[it][i].x, v[it][i].y, v[it][i].z, v[it][i].w};
#pragma unroll
                    for (int c = 0; c < 4; c++) {
                        const float d0 = bf_lo(w[c]), d1 = bf_hi(w[c]);
                        s0 += d0; s1 += d1;
                        q0 = fmaf(d0, d0, q0);
                        q1 = fmaf(d1, d1, q1);
                    }
                }
                float s = s0 + s1, q = q0 + q1;
#pragma unroll
                for (int o = 1; o < 8; o <<= 1) {
                    s += __shfl_xor_sync(0xffffffffu, s, o);
                    q += __shfl_xor_sync(0xffffffffu, q, o);
                }
                if (it == 0 && tid == 0) TL(0, 3);
                const float mean = s * (1.0f / D_);
                const float var = rbf(fmaxf(fmaf(-mean, mean, q * (1.0f / D_)), 0.f));
                const float den = rbf(sqrtf(rbf(var + 1e-5f)));
                const float rinv = 1.0f / den;
                const float rhi = rbf(rinv);
                const uint32_t m2 = pack_bf16(mean, mean), rhi2 = pack_bf16(rhi, rhi), rlo2 = pack_bf16(rinv - rhi, rinv - rhi);
                const uint32_t dst = sb + S1_XN + row * 128 + ((l8 ^ (row & 7)) << 4);
#pragma unroll
                for (int i = 0; i < 7; i++) {
                    const uint32_t w[4] = {v[it][i].x, v[it][i].y, v[it][i].z, v[it][i].w};
                    uint32_t o[4];
#pragma unroll
                    for (int c = 0; c < 4; c++) {
                        const uint32_t xc = hsub2(w[c], m2);
                        o[c] = hfma2(xc, rhi2, hmul2(xc, rlo2));
                    }
                    asm volatile("st.shared.v4.b32 [%0], {%1, %2, %3, %4};" ::"r"(dst + i * 16384), "r"(o[0]), "r"(o[1]), "r"(o[2]), "r"(o[3]) : "memory");
                }
            }
        }
        fence_async();
        __syncthreads();
        if (tid == 0) TL(0, 2);
    }

    if (warp >= 8) {
        asm volatile("setmaxnreg.dec.sync.aligned.u32 40;");
        if (warp == 8) {
            if (lane == 0) {
                int st = 0;
                uint32_t ph = 0;
                for (int p = 0; p < npass; p++) {
                    const int slab = pass_slab(j, p);
                    for (int kb = p ? 0 : S1_STAGES; kb < 7; kb++) {
                        mbar_wait(sb + BAR_E1 + 8 * st, ph);
                        const uint32_t dst = sb + S1_B + st * 16384 + rank * 8192;
                        const uint32_t fb = sb + BAR_F1 + 8 * st;
                        mbar_expect(fb, 16384);
                        if (slab >= 0) {
                            tma_load_mc(dst, rank ? &tm.wu : &tm.wg, fb, slab * 64, kb * 64);
                        } else {
                            const int a = 2 * j + rank;
                            tma_load_mc(dst, a < 7 ? &tm.hre : &tm.him, fb, kb * 64, (a < 7 ? a : a - 7) * 64);
                        }
                        if (++st == S1_STAGES) { st = 0; ph ^= 1; }
                        if (p == 1 && part < 2) {
                            for (int q = kb; q < 16; q += 7) tma_prefetch(part ? &tm.sim : &tm.sre, (2 * q + n) * 64, rb * 128);
                        }
                    }
                }
                if (part < 3) {
                    mbar_wait(sb + BAR_S1DONE, 0);
                    TL(0, 24);
                    st = 0; ph = 1;
                    if (part < 2) {
                        const CUtensorMap* ma = part ? &tm.sim : &tm.sre;
                        for (int g = 0; g < 32; g++) {
                            mbar_wait(sb + BAR_E2 + 8 * st, ph);
                            const uint32_t dst = sb + st * Y_STAGE;
                            const uint32_t fb = sb + BAR_F2 + 8 * st;
                            mbar_expect(fb, Y_STAGE);
                            tma_load(dst, ma, fb, g * 64, rb * 128);
                            dep_wait(sb, (g >> 1) + 1);
                            tma_load_mc(dst + 16384 + rank * 14336, &tm.abT, fb, g * 64, part * 448 + n * 224 + rank * 112);
                            if (++st == Y_STAGES) { st = 0; ph ^= 1; }
                        }
                    } else {
                        for (int g = 0; g < 28; g++) {
                            mbar_wait(sb + BAR_E2 + 8 * st, ph);
                            const uint32_t dst = sb + st * F_STAGE;
                            const uint32_t fb = sb + BAR_F2 + 8 * st;
                            mbar_expect(fb, F_STAGE);
                            tma_load_mc(dst + 16384 + (2 * rank) * 8192, &tm.wd, fb, n * 224 + (2 * rank) * 64, g * 64);
                            tma_load_mc(dst + 16384 + (2 * rank + 1) * 8192, &tm.wd, fb, n * 224 + (2 * rank + 1) * 64, g * 64);
                            dep_wait(sb, g + 1);
                            tma_load(dst, &tm.h, fb, g * 64, rb * 128);
                            if (++st == F_STAGES) { st = 0; ph ^= 1; }
                        }
                    }
                }
            }
        } else if (warp == 9) {
            if (part < 3) {
                const int ndep = part < 2 ? 16 : 29;
                const unsigned int epoch = *(volatile unsigned int*)&g_fl.done / gridDim.x + 1;
                const unsigned int* f = part < 2 ? &g_fl.ab[lane & 15] : (lane < 28 ? &g_fl.h[rb * 28 + lane] : &g_fl.y[rb * 2 + n]);
                const unsigned int target = (part < 2 ? 7 * 5 : (lane < 27 ? 1 : (lane == 27 ? 2 : 16))) * epoch;
                bool ok = lane >= ndep;
                int published = 0;
                for (int spins = 0; published < ndep && spins < (1 << 22); spins++) {
                    if (!ok) {
                        unsigned int v;
                        asm volatile("ld.acquire.gpu.global.u32 %0, [%1];" : "=r"(v) : "l"(f) : "memory");
                        ok = (int)(v - target) >= 0;
                    }
                    const unsigned int m = __ballot_sync(0xffffffffu, ok);
                    const int cnt = min(__ffs(~m) - 1, ndep);
                    if (m == 0xffffffffu || cnt > published) {
                        published = (m == 0xffffffffu) ? ndep : cnt;
                        fence_async_all();
                        __syncwarp();
                        if (lane == 0) asm volatile("st.release.cta.shared.u32 [%0], %1;" ::"r"(sb + DEP_CNT), "r"(published) : "memory");
                    }
                }
                if (published < ndep && lane == 0)
                    asm volatile("st.release.cta.shared.u32 [%0], %1;" ::"r"(sb + DEP_CNT), "r"(ndep) : "memory");
            }
        } else if (warp == 10) {
            if (lane == 0) {
                for (int p = 0; p < npass; p++) {
                    const int slab = pass_slab(j, p);
                    mbar_wait(sb + BAR_SF, p & 1);
                    if (slab == 27) tma_store(&tm.h64, sb + STG, slab * 64, rb * 128 + n * 64);
                    else if (slab >= 0) tma_store(&tm.h, sb + STG, slab * 64, rb * 128);
                    else tma_store(&tm.abT_st, sb + STG, rb * 128, j * 128);
                    bulk_commit();
                    bulk_wait_read0();
                    asm volatile("st.release.cta.shared.u32 [%0], %1;" ::"r"(sb + SE_CNT), "r"(p + 1) : "memory");
                    bulk_wait0();
                    fence_async_all();
                    flag_add(slab >= 0 ? &g_fl.h[rb * 28 + slab] : &g_fl.ab[rb]);
                }
            }
        }
        __syncwarp();
    } else {
        asm volatile("setmaxnreg.inc.sync.aligned.u32 232;");
        const int wg = warp >> 2, wl = warp & 3, wtid = tid & 127;
        const int qd = lane & 3;
        {
            float acc[2][64];
            for (int p = wg; p < npass; p += 2) {
                const int slab = pass_slab(j, p);
                if (p > 0) bar_sync(4 + (p & 1), 256);
                const int handoff = (p + 1 < npass) ? 4 + ((p + 1) & 1) : 0;
                if (slab == 27) s1_mainloop<2>(acc, sb, p, lane, handoff, n);
                else if (slab >= 0) s1_mainloop<1>(acc, sb, p, lane, handoff);
                else s1_mainloop<0>(acc, sb, p, lane, handoff);
                if (p + 2 >= npass && part < 3 && lane == 0) mbar_arrive_both(sb + BAR_S1DONE);
                if (wtid == 0 && p < 4) TL(0, 4 + p);

                const uint32_t srow = sb + STG + (wl * 16 + (lane & 7) + ((lane >> 3) & 1) * 8) * 128;
                if (slab >= 0) {
                    uint32_t hv[2][16];
#pragma unroll
                    for (int mh = 0; mh < 2; mh++) {
                        if (mh == 0 || slab != 27) {
#pragma unroll
                            for (int i = 0; i < 16; i++) {
                                const uint32_t g2 = pack_bf16(acc[mh][2 * i], acc[mh][2 * i + 1]);
                                const uint32_t u2 = pack_bf16(acc[mh][32 + 2 * i], acc[mh][32 + 2 * i + 1]);
                                const uint32_t a2 = pack_bf16(gelu_tanh(bf_lo(g2)), gelu_tanh(bf_hi(g2)));
                                hv[mh][i] = hmul2(a2, u2);
                            }
                        }
                    }
                    cnt_wait(sb + SE_CNT, p);
#pragma unroll
                    for (int mh = 0; mh < 2; mh++) {
                        if (mh == 0 || slab != 27) {
#pragma unroll
                            for (int jj = 0; jj < 8; jj += 2)
                                stmat4(srow + mh * 8192 + (((jj + (lane >> 4)) ^ (lane & 7)) << 4),
                                       hv[mh][2 * jj], hv[mh][2 * jj + 1], hv[mh][2 * jj + 2], hv[mh][2 * jj + 3]);
                        }
                    }
                } else {
#pragma unroll
                    for (int mh = 0; mh < 2; mh++) {
#pragma unroll
                        for (int jj = 0; jj < 8; jj += 2) {
                            const int o = jj * 4;
                            stmat4(srow + mh * 8192 + (((jj + (lane >> 4)) ^ (lane & 7)) << 4),
                                   pack_bf16(acc[mh][o], acc[mh][o + 1]), pack_bf16(acc[mh][o + 2], acc[mh][o + 3]),
                                   pack_bf16(acc[mh][o + 4], acc[mh][o + 5]), pack_bf16(acc[mh][o + 6], acc[mh][o + 7]));
                        }
                    }
                    fence_async();
                    __syncwarp();
                    if (lane == 0) mbar_arrive(sb + BAR_SF);
                    __nv_bfloat16* dst = g_abT + (size_t)(j * 128 + wl * 16 + (lane >> 2)) * ABP + rb * 128 + 64 + qd * 8;
#pragma unroll
                    for (int mh = 0; mh < 2; mh++) {
#pragma unroll
                        for (int hh = 0; hh < 2; hh++) {
#pragma unroll
                            for (int g4 = 0; g4 < 2; g4++) {
                                uint32_t r[4];
#pragma unroll
                                for (int t = 0; t < 4; t++) {
                                    const int o = 32 + (g4 * 4 + t) * 4 + hh * 2;
                                    r[t] = pack_bf16(acc[mh][o], acc[mh][o + 1]);
                                }
                                quad_transpose(r, qd);
                                __stcg(reinterpret_cast<uint4*>(dst + (size_t)(mh * 64 + hh * 8) * ABP + g4 * 32), make_uint4(r[0], r[1], r[2], r[3]));
                            }
                        }
                    }
                    __threadfence();
                    __syncwarp();
                    if (lane == 0) flag_add(&g_fl.ab[rb]);
                }
                if (slab >= 0) {
                    fence_async();
                    __syncwarp();
                    if (lane == 0) mbar_arrive(sb + BAR_SF);
                }
                if (wtid == 0 && p < 4) TL(0, 10 + p);
            }
        }
        if (wtid == 0) TL(0, 20 + wg);
        if (part < 3) {
            {
                float acc[112];
                const size_t base = (size_t)(rb * 128 + wg * 64 + wl * 16 + (lane >> 2)) * D_ + n * 224 + qd * 8;
                if (part < 2) {
                    s2_mainloop<0>(acc, sb, wg, lane);
                    if (tid == 0) TL(0, 25);
                    uint4* dst = g_y + (size_t)((part * 32 + rb * 2 + n) * 14) * 256 + tid;
#pragma unroll
                    for (int i = 0; i < 14; i++)
                        __stcg(dst + i * 256, make_uint4(pack_bf16(acc[8 * i], acc[8 * i + 1]), pack_bf16(acc[8 * i + 2], acc[8 * i + 3]),
                                                         pack_bf16(acc[8 * i + 4], acc[8 * i + 5]), pack_bf16(acc[8 * i + 6], acc[8 * i + 7])));
                    __threadfence();
                    __syncwarp();
                    if (lane == 0) flag_add(&g_fl.y[rb * 2 + n]);
                } else {
                    uint4 xv[14];
#pragma unroll
                    for (int i = 0; i < 14; i++)
                        xv[i] = __ldg(reinterpret_cast<const uint4*>(pt.x + base + (i / 7) * 8 * D_ + (i % 7) * 32));
                    s2_mainloop<1>(acc, sb, wg, lane);
                    if (tid == 0) TL(0, 25);
                    dep_wait(sb, 29);
                    if (tid == 0) TL(0, 26);
                    const uint4* ysrc = g_y + (size_t)((rb * 2 + n) * 14) * 256 + tid;
                    uint4 yr[14], yi[14];
#pragma unroll
                    for (int i = 0; i < 14; i++) yr[i] = __ldcg(ysrc + i * 256);
                    uint32_t sg[56];
#pragma unroll
                    for (int i = 0; i < 56; i++) {
                        const uint32_t f2 = pack_bf16(acc[2 * i], acc[2 * i + 1]);
                        sg[i] = pack_bf16(silu(bf_lo(f2)), silu(bf_hi(f2)));
                    }
#pragma unroll
                    for (int i = 0; i < 14; i++) yi[i] = __ldcg(ysrc + (32 * 14 + i) * 256);
#pragma unroll
                    for (int i = 0; i < 14; i++) {
                        sg[4 * i + 0] = hmul2(hsub2(yr[i].x, yi[i].x), sg[4 * i + 0]);
                        sg[4 * i + 1] = hmul2(hsub2(yr[i].y, yi[i].y), sg[4 * i + 1]);
                        sg[4 * i + 2] = hmul2(hsub2(yr[i].z, yi[i].z), sg[4 * i + 2]);
                        sg[4 * i + 3] = hmul2(hsub2(yr[i].w, yi[i].w), sg[4 * i + 3]);
                    }
#pragma unroll
                    for (int hh = 0; hh < 2; hh++) {
#pragma unroll
                        for (int g4 = 0; g4 < 7; g4++) {
                            uint32_t r[4];
#pragma unroll
                            for (int t = 0; t < 4; t++) r[t] = sg[(g4 * 4 + t) * 2 + hh];
                            quad_transpose(r, qd);
                            const uint4 xx = xv[hh * 7 + g4];
                            *reinterpret_cast<uint4*>(pt.out + base + hh * 8 * D_ + g4 * 32) =
                                make_uint4(hadd2(xx.x, r[0]), hadd2(xx.y, r[1]), hadd2(xx.z, r[2]), hadd2(xx.w, r[3]));
                        }
                    }
                }
            }
        }
    }
    if (tid == 0) TL(0, 29);
    __syncthreads();
    if (tid == 0) {
        TL(0, 30);
        atomicAdd(&g_fl.done, 1u);
    }
}

typedef CUresult (*EncFn)(CUtensorMap*, CUtensorMapDataType, cuuint32_t, void*, const cuuint64_t*, const cuuint64_t*,
                          const cuuint32_t*, const cuuint32_t*, CUtensorMapInterleave, CUtensorMapSwizzle,
                          CUtensorMapL2promotion, CUtensorMapFloatOOBfill);

void make_map(EncFn enc, CUtensorMap* m, const void* ptr, int rows, int cols, int box_rows, int box_cols, int pitch = 0) {
    const bool swz = true;
    cuuint64_t gd[2] = {(cuuint64_t)cols, (cuuint64_t)rows};
    cuuint64_t gs[1] = {(cuuint64_t)(pitch ? pitch : cols) * 2};
    cuuint32_t bx[2] = {(cuuint32_t)box_cols, (cuuint32_t)box_rows};
    cuuint32_t es[2] = {1, 1};
    enc(m, CU_TENSOR_MAP_DATA_TYPE_BFLOAT16, 2, const_cast<void*>(ptr), gd, gs, bx, es, CU_TENSOR_MAP_INTERLEAVE_NONE,
        swz ? CU_TENSOR_MAP_SWIZZLE_128B : CU_TENSOR_MAP_SWIZZLE_NONE, CU_TENSOR_MAP_L2_PROMOTION_L2_128B,
        CU_TENSOR_MAP_FLOAT_OOB_FILL_NONE);
}

}

extern "C" void kernel_launch(void* const* d_in, const int* in_sizes, int n_in, void* d_out, int out_size) {
    Ptrs pt;
    pt.x = (const __nv_bfloat16*)d_in[0];
    pt.hre = (const __nv_bfloat16*)d_in[3];
    pt.him = (const __nv_bfloat16*)d_in[4];
    pt.wg = (const __nv_bfloat16*)d_in[6];
    pt.wu = (const __nv_bfloat16*)d_in[7];
    pt.wd = (const __nv_bfloat16*)d_in[8];
    pt.out = (__nv_bfloat16*)d_out;

    void* fn = nullptr;
    cudaDriverEntryPointQueryResult qr;
    cudaGetDriverEntryPoint("cuTensorMapEncodeTiled", &fn, cudaEnableDefault, &qr);
    EncFn enc = (EncFn)fn;
    void *p_abT, *p_h;
    cudaGetSymbolAddress(&p_abT, g_abT);
    cudaGetSymbolAddress(&p_h, g_h);

    Maps tm;
    make_map(enc, &tm.wg, d_in[6], D_, F_, 64, 64);
    make_map(enc, &tm.wu, d_in[7], D_, F_, 64, 64);
    make_map(enc, &tm.hre, d_in[3], D_, D_, 64, 64);
    make_map(enc, &tm.him, d_in[4], D_, D_, 64, 64);
    make_map(enc, &tm.h, p_h, S_, F_, 128, 64);
    make_map(enc, &tm.h64, p_h, S_, F_, 64, 64);
    make_map(enc, &tm.abT, p_abT, 896, S_, 112, 64, ABP);
    make_map(enc, &tm.abT_st, p_abT, 896, S_, 128, 64, ABP);
    make_map(enc, &tm.sre, d_in[1], S_, S_, 128, 64);
    make_map(enc, &tm.sim, d_in[2], S_, S_, 128, 64);
    make_map(enc, &tm.wd, d_in[8], F_, D_, 64, 64);

    cudaFuncSetAttribute(fused_kernel, cudaFuncAttributeMaxDynamicSharedMemorySize, SMEM_BYTES);

    cudaLaunchAttribute at[1];
    at[0].id = cudaLaunchAttributeClusterDimension;
    at[0].val.clusterDim.x = 2; at[0].val.clusterDim.y = 1; at[0].val.clusterDim.z = 1;
    cudaLaunchConfig_t cfg = {};
    cfg.gridDim = dim3(128); cfg.blockDim = dim3(384); cfg.stream = cudaStreamPerThread;
    cfg.attrs = at; cfg.numAttrs = 1;
    cfg.dynamicSmemBytes = SMEM_BYTES;
    cudaLaunchKernelEx(&cfg, fused_kernel, pt, tm);
}
```

```cpp
#include <cuda_runtime.h>
#include <cuda_bf16.h>
#include <cuda.h>
#include <stdint.h>

namespace {

constexpr int S_ = 2048, D_ = 448, F_ = 1792;

constexpr int ABP = 2048 + 64;
__device__ __align__(1024) __nv_bfloat16 g_abT[896 * ABP];
__device__ __align__(1024) __nv_bfloat16 g_h[2048 * 1792];
__device__ __align__(1024) uint4 g_y[2 * 32 * 14 * 256];
struct Flags {
    unsigned int ab[16];
    unsigned int h[16 * 28];
    unsigned int y[32];
    unsigned int done;
};
__device__ Flags g_fl;

#define TL(k, i) do {} while (0)
__device__ __forceinline__ uint32_t s2u(const void* p) { return (uint32_t)__cvta_generic_to_shared(p); }
__device__ __forceinline__ void mbar_init(uint32_t b, int c) {
    asm volatile("mbarrier.init.shared::cta.b64 [%0], %1;" ::"r"(b), "r"(c));
}
__device__ __forceinline__ void mbar_expect(uint32_t b, uint32_t bytes) {
    asm volatile("mbarrier.arrive.expect_tx.shared::cta.b64 _, [%0], %1;" ::"r"(b), "r"(bytes) : "memory");
}
__device__ __forceinline__ void mbar_wait(uint32_t b, uint32_t ph) {
    uint32_t ok;
    do {
        asm volatile("{\n.reg .pred p;\nmbarrier.try_wait.parity.shared::cta.b64 p, [%1], %2;\nselp.u32 %0, 1, 0, p;\n}"
                     : "=r"(ok) : "r"(b), "r"(ph) : "memory");
    } while (!ok);
}
__device__ __forceinline__ void mbar_arrive_both(uint32_t b) {
    asm volatile("{\n.reg .b32 r0, r1;\n"
                 "mapa.shared::cluster.u32 r0, %0, 0;\n"
                 "mapa.shared::cluster.u32 r1, %0, 1;\n"
                 "mbarrier.arrive.shared::cluster.b64 _, [r0];\n"
                 "mbarrier.arrive.shared::cluster.b64 _, [r1];\n}"
                 ::"r"(b) : "memory");
}
__device__ __forceinline__ void tma_load(uint32_t dst, const CUtensorMap* m, uint32_t bar, int c0, int c1) {
    asm volatile("cp.async.bulk.tensor.2d.shared::cluster.global.mbarrier::complete_tx::bytes [%0], [%1, {%3, %4}], [%2];"
                 ::"r"(dst), "l"(m), "r"(bar), "r"(c0), "r"(c1) : "memory");
}
__device__ __forceinline__ void tma_load_mc(uint32_t dst, const CUtensorMap* m, uint32_t bar, int c0, int c1) {
    asm volatile("cp.async.bulk.tensor.2d.shared::cluster.global.mbarrier::complete_tx::bytes.multicast::cluster [%0], [%1, {%3, %4}], [%2], %5;"
                 ::"r"(dst), "l"(m), "r"(bar), "r"(c0), "r"(c1), "h"((uint16_t)3) : "memory");
}
__device__ __forceinline__ void tma_store(const CUtensorMap* m, uint32_t src, int c0, int c1) {
    asm volatile("cp.async.bulk.tensor.2d.global.shared::cta.bulk_group [%0, {%2, %3}], [%1];"
                 ::"l"(m), "r"(src), "r"(c0), "r"(c1) : "memory");
}
__device__ __forceinline__ void bulk_commit() { asm volatile("cp.async.bulk.commit_group;" ::: "memory"); }
__device__ __forceinline__ void bulk_wait_read0() { asm volatile("cp.async.bulk.wait_group.read 0;" ::: "memory"); }
__device__ __forceinline__ void bulk_wait0() { asm volatile("cp.async.bulk.wait_group 0;" ::: "memory"); }
__device__ __forceinline__ void fence_async() { asm volatile("fence.proxy.async.shared::cta;" ::: "memory"); }
__device__ __forceinline__ void fence_async_all() { asm volatile("fence.proxy.async;" ::: "memory"); }
__device__ __forceinline__ void cluster_sync() {
    asm volatile("barrier.cluster.arrive.release.aligned;\nbarrier.cluster.wait.acquire.aligned;" ::: "memory");
}
__device__ __forceinline__ void bar_sync(int id, int n) { asm volatile("bar.sync %0, %1;" ::"r"(id), "r"(n) : "memory"); }
__device__ __forceinline__ void wg_arrive() { asm volatile("wgmma.fence.sync.aligned;" ::: "memory"); }
__device__ __forceinline__ void wg_commit() { asm volatile("wgmma.commit_group.sync.aligned;" ::: "memory"); }
template <int N> __device__ __forceinline__ void wg_wait() { asm volatile("wgmma.wait_group.sync.aligned %0;" ::"n"(N) : "memory"); }
__device__ __forceinline__ void stmat4(uint32_t a, uint32_t r0, uint32_t r1, uint32_t r2, uint32_t r3) {
    asm volatile("stmatrix.sync.aligned.m8n8.x4.shared.b16 [%0], {%1, %2, %3, %4};" ::"r"(a), "r"(r0), "r"(r1), "r"(r2), "r"(r3) : "memory");
}
__device__ __forceinline__ void stmat4t(uint32_t a, uint32_t r0, uint32_t r1, uint32_t r2, uint32_t r3) {
    asm volatile("stmatrix.sync.aligned.m8n8.x4.trans.shared.b16 [%0], {%1, %2, %3, %4};" ::"r"(a), "r"(r0), "r"(r1), "r"(r2), "r"(r3) : "memory");
}
__device__ __forceinline__ void ldmat4(uint32_t a, uint32_t (&r)[4]) {
    asm volatile("ldmatrix.sync.aligned.m8n8.x4.shared.b16 {%0, %1, %2, %3}, [%4];"
                 : "=r"(r[0]), "=r"(r[1]), "=r"(r[2]), "=r"(r[3]) : "r"(a) : "memory");
}
__device__ __forceinline__ void flag_add(unsigned int* f) {
    asm volatile("red.release.gpu.global.add.u32 [%0], 1;" ::"l"(f) : "memory");
}
__device__ __forceinline__ void flag_wait(const unsigned int* f, unsigned int target) {
    unsigned int v;
    int spins = 0;
    while (true) {
        asm volatile("ld.acquire.gpu.global.u32 %0, [%1];" : "=r"(v) : "l"(f) : "memory");
        if ((int)(v - target) >= 0 || ++spins > (1 << 22)) break;
    }
}
__device__ __forceinline__ void quad_transpose(uint32_t (&r)[4], int q) {
    const bool o1 = q & 1, o2 = q & 2;
    uint32_t a = o1 ? r[0] : r[1], b = o1 ? r[2] : r[3];
    a = __shfl_xor_sync(0xffffffffu, a, 1);
    b = __shfl_xor_sync(0xffffffffu, b, 1);
    if (o1) { r[0] = a; r[2] = b; } else { r[1] = a; r[3] = b; }
    a = o2 ? r[0] : r[2]; b = o2 ? r[1] : r[3];
    a = __shfl_xor_sync(0xffffffffu, a, 2);
    b = __shfl_xor_sync(0xffffffffu, b, 2);
    if (o2) { r[0] = a; r[1] = b; } else { r[2] = a; r[3] = b; }
}
__device__ __forceinline__ uint32_t movmat_t(uint32_t v) {
    uint32_t r;
    asm volatile("movmatrix.sync.aligned.m8n8.trans.b16 %0, %1;" : "=r"(r) : "r"(v));
    return r;
}
__device__ __forceinline__ uint64_t mkdesc(uint32_t addr, uint32_t lbo, uint32_t sbo) {
    return (uint64_t)((addr & 0x3FFFF) >> 4) | ((uint64_t)(lbo >> 4) << 16) | ((uint64_t)(sbo >> 4) << 32) | (1ull << 62);
}
__device__ __forceinline__ uint32_t pack_bf16(float lo, float hi) {
    uint32_t r;
    asm("cvt.rn.bf16x2.f32 %0, %1, %2;" : "=r"(r) : "f"(hi), "f"(lo));
    return r;
}
__device__ __forceinline__ uint32_t hsub2(uint32_t a, uint32_t b) { uint32_t r; asm("sub.rn.bf16x2 %0, %1, %2;" : "=r"(r) : "r"(a), "r"(b)); return r; }
__device__ __forceinline__ uint32_t hadd2(uint32_t a, uint32_t b) { uint32_t r; asm("add.rn.bf16x2 %0, %1, %2;" : "=r"(r) : "r"(a), "r"(b)); return r; }
__device__ __forceinline__ uint32_t hmul2(uint32_t a, uint32_t b) { uint32_t r; asm("mul.rn.bf16x2 %0, %1, %2;" : "=r"(r) : "r"(a), "r"(b)); return r; }
__device__ __forceinline__ uint32_t hfma2(uint32_t a, uint32_t b, uint32_t c) { uint32_t r; asm("fma.rn.bf16x2 %0, %1, %2, %3;" : "=r"(r) : "r"(a), "r"(b), "r"(c)); return r; }
__device__ __forceinline__ float bf_lo(uint32_t u) { return __uint_as_float(u << 16); }
__device__ __forceinline__ float bf_hi(uint32_t u) { return __uint_as_float(u & 0xffff0000u); }
__device__ __forceinline__ float rbf(float v) { return __bfloat162float(__float2bfloat16_rn(v)); }
__device__ __forceinline__ float tanh_fast(float x) { float r; asm("tanh.approx.f32 %0, %1;" : "=f"(r) : "f"(x)); return r; }
__device__ __forceinline__ float gelu_tanh(float x) {
    float u = x * fmaf(x * x, 0.0356774081f, 0.7978845608f);
    float hx = 0.5f * x;
    return fmaf(hx, tanh_fast(u), hx);
}
__device__ __forceinline__ float silu(float f) { const float hf = 0.5f * f; return fmaf(hf, tanh_fast(hf), hf); }

template <int TB>
__device__ __forceinline__ void wgmma_n128(float (&d)[64], uint64_t da, uint64_t db, int scaleD) {
    asm volatile("{\n.reg .pred p;\nsetp.ne.b32 p, %66, 0;\n"
        "wgmma.mma_async.sync.aligned.m64n128k16.f32.bf16.bf16 {%0, %1, %2, %3, %4, %5, %6, %7, %8, %9, %10, %11, %12, %13, %14, %15, %16, %17, %18, %19, %20, %21, %22, %23, %24, %25, %26, %27, %28, %29, %30, %31, %32, %33, %34, %35, %36, %37, %38, %39, %40, %41, %42, %43, %44, %45, %46, %47, %48, %49, %50, %51, %52, %53, %54, %55, %56, %57, %58, %59, %60, %61, %62, %63}, %64, %65, p, 1, 1, 0, %67;\n}\n"
        : "+f"(d[0]), "+f"(d[1]), "+f"(d[2]), "+f"(d[3]), "+f"(d[4]), "+f"(d[5]), "+f"(d[6]), "+f"(d[7]), "+f"(d[8]), "+f"(d[9]), "+f"(d[10]), "+f"(d[11]), "+f"(d[12]), "+f"(d[13]), "+f"(d[14]), "+f"(d[15]), "+f"(d[16]), "+f"(d[17]), "+f"(d[18]), "+f"(d[19]), "+f"(d[20]), "+f"(d[21]), "+f"(d[22]), "+f"(d[23]), "+f"(d[24]), "+f"(d[25]), "+f"(d[26]), "+f"(d[27]), "+f"(d[28]), "+f"(d[29]), "+f"(d[30]), "+f"(d[31]), "+f"(d[32]), "+f"(d[33]), "+f"(d[34]), "+f"(d[35]), "+f"(d[36]), "+f"(d[37]), "+f"(d[38]), "+f"(d[39]), "+f"(d[40]), "+f"(d[41]), "+f"(d[42]), "+f"(d[43]), "+f"(d[44]), "+f"(d[45]), "+f"(d[46]), "+f"(d[47]), "+f"(d[48]), "+f"(d[49]), "+f"(d[50]), "+f"(d[51]), "+f"(d[52]), "+f"(d[53]), "+f"(d[54]), "+f"(d[55]), "+f"(d[56]), "+f"(d[57]), "+f"(d[58]), "+f"(d[59]), "+f"(d[60]), "+f"(d[61]), "+f"(d[62]), "+f"(d[63])
        : "l"(da), "l"(db), "r"(scaleD), "n"(TB));
}
template <int TB>
__device__ __forceinline__ void wgmma_n224(float (&d)[112], uint64_t da, uint64_t db, int scaleD) {
    asm volatile("{\n.reg .pred p;\nsetp.ne.b32 p, %114, 0;\n"
        "wgmma.mma_async.sync.aligned.m64n224k16.f32.bf16.bf16 {%0, %1, %2, %3, %4, %5, %6, %7, %8, %9, %10, %11, %12, %13, %14, %15, %16, %17, %18, %19, %20, %21, %22, %23, %24, %25, %26, %27, %28, %29, %30, %31, %32, %33, %34, %35, %36, %37, %38, %39, %40, %41, %42, %43, %44, %45, %46, %47, %48, %49, %50, %51, %52, %53, %54, %55, %56, %57, %58, %59, %60, %61, %62, %63, %64, %65, %66, %67, %68, %69, %70, %71, %72, %73, %74, %75, %76, %77, %78, %79, %80, %81, %82, %83, %84, %85, %86, %87, %88, %89, %90, %91, %92, %93, %94, %95, %96, %97, %98, %99, %100, %101, %102, %103, %104, %105, %106, %107, %108, %109, %110, %111}, %112, %113, p, 1, 1, 0, %115;\n}\n"
        : "+f"(d[0]), "+f"(d[1]), "+f"(d[2]), "+f"(d[3]), "+f"(d[4]), "+f"(d[5]), "+f"(d[6]), "+f"(d[7]), "+f"(d[8]), "+f"(d[9]), "+f"(d[10]), "+f"(d[11]), "+f"(d[12]), "+f"(d[13]), "+f"(d[14]), "+f"(d[15]), "+f"(d[16]), "+f"(d[17]), "+f"(d[18]), "+f"(d[19]), "+f"(d[20]), "+f"(d[21]), "+f"(d[22]), "+f"(d[23]), "+f"(d[24]), "+f"(d[25]), "+f"(d[26]), "+f"(d[27]), "+f"(d[28]), "+f"(d[29]), "+f"(d[30]), "+f"(d[31]), "+f"(d[32]), "+f"(d[33]), "+f"(d[34]), "+f"(d[35]), "+f"(d[36]), "+f"(d[37]), "+f"(d[38]), "+f"(d[39]), "+f"(d[40]), "+f"(d[41]), "+f"(d[42]), "+f"(d[43]), "+f"(d[44]), "+f"(d[45]), "+f"(d[46]), "+f"(d[47]), "+f"(d[48]), "+f"(d[49]), "+f"(d[50]), "+f"(d[51]), "+f"(d[52]), "+f"(d[53]), "+f"(d[54]), "+f"(d[55]), "+f"(d[56]), "+f"(d[57]), "+f"(d[58]), "+f"(d[59]), "+f"(d[60]), "+f"(d[61]), "+f"(d[62]), "+f"(d[63]), "+f"(d[64]), "+f"(d[65]), "+f"(d[66]), "+f"(d[67]), "+f"(d[68]), "+f"(d[69]), "+f"(d[70]), "+f"(d[71]), "+f"(d[72]), "+f"(d[73]), "+f"(d[74]), "+f"(d[75]), "+f"(d[76]), "+f"(d[77]), "+f"(d[78]), "+f"(d[79]), "+f"(d[80]), "+f"(d[81]), "+f"(d[82]), "+f"(d[83]), "+f"(d[84]), "+f"(d[85]), "+f"(d[86]), "+f"(d[87]), "+f"(d[88]), "+f"(d[89]), "+f"(d[90]), "+f"(d[91]), "+f"(d[92]), "+f"(d[93]), "+f"(d[94]), "+f"(d[95]), "+f"(d[96]), "+f"(d[97]), "+f"(d[98]), "+f"(d[99]), "+f"(d[100]), "+f"(d[101]), "+f"(d[102]), "+f"(d[103]), "+f"(d[104]), "+f"(d[105]), "+f"(d[106]), "+f"(d[107]), "+f"(d[108]), "+f"(d[109]), "+f"(d[110]), "+f"(d[111])
        : "l"(da), "l"(db), "r"(scaleD), "n"(TB));
}

constexpr int S1_STAGES = 6;
constexpr int S1_XN = 0;
constexpr int S1_B = 7 * 16384;
constexpr int STG = S1_B + S1_STAGES * 16384;
constexpr int Y_STAGES = 4, Y_STAGE = 45056;
constexpr int F_STAGES = 4, F_STAGE = 49152;
constexpr int BAR = STG + 16384;
constexpr int BAR_F1 = BAR, BAR_E1 = BAR + 56, BAR_F2 = BAR + 112, BAR_E2 = BAR + 152, BAR_S1DONE = BAR + 192;
constexpr int BAR_SF = BAR + 208;
constexpr int SE_CNT = BAR + 216;
constexpr int DEP_CNT = BAR + 200;
constexpr int SMEM_BYTES = BAR + 256 + 1024;
constexpr int TPITCH = 464;

__device__ __forceinline__ int n_passes(int j) { return j < 4 ? 2 : (j < 6 ? 4 : 10); }
__device__ __forceinline__ int pass_slab(int j, int p) {
    if (p == 0) return j < 7 ? -1 : 0;
    if (p == 1) return 1 + j;
    if (p < 4) return 4 * p - 3 + j;
    if (p == 9) return 27;
    return 17 + 2 * (p - 4) + (j - 6);
}

template <int TB>
__device__ __forceinline__ void s1_mainloop(float (&acc)[2][64], uint32_t sb, int p, int lane, int handoff, int half = 0) {
    int st = (p * 7) % S1_STAGES;
    uint32_t ph = ((p * 7) / S1_STAGES) & 1;
    int prev = 0;
    uint64_t dx = mkdesc(sb + S1_XN + half * 8192, 16, 1024);
    const uint64_t dw0 = TB ? mkdesc(sb + S1_B, 8192, 1024) : mkdesc(sb + S1_B, 16, 1024);
    const int nrel = lane == 0 ? (handoff ? 7 : 7 - S1_STAGES) : 0;
#pragma unroll 1
    for (int kb = 0; kb < 7; kb++) {
        mbar_wait(sb + BAR_F1 + 8 * st, ph);
        if (kb == 6 && handoff) asm volatile("bar.arrive %0, 256;" ::"r"(handoff) : "memory");
        const uint64_t dw = dw0 + st * 1024;
        wg_arrive();
#pragma unroll
        for (int s = 0; s < 4; s++) {
            if (TB == 2) {
                wgmma_n128<1>(acc[0], dx + s * 2, dw + s * 128, kb | s);
            } else if (TB) {
                wgmma_n128<1>(acc[0], dx + s * 2, dw + s * 128, kb | s);
                wgmma_n128<1>(acc[1], dx + 512 + s * 2, dw + s * 128, kb | s);
            } else {
                wgmma_n128<0>(acc[0], dw + s * 2, dx + s * 2, kb | s);
                wgmma_n128<0>(acc[1], dw + 512 + s * 2, dx + s * 2, kb | s);
            }
        }
        wg_commit();
        wg_wait<1>();
        if (kb > 0 && kb <= nrel) mbar_arrive_both(sb + BAR_E1 + 8 * prev);
        prev = st;
        dx += 1024;
        if (++st == S1_STAGES) { st = 0; ph ^= 1; }
    }
    wg_wait<0>();
    if (TB && nrel == 7) mbar_arrive_both(sb + BAR_E1 + 8 * prev);
}

template <int TB>
__device__ __forceinline__ void s2_mainloop(float (&acc)[112], uint32_t sb, int wg, int lane) {
    constexpr int NST = TB ? F_STAGES : Y_STAGES, SSZ = TB ? F_STAGE : Y_STAGE, NKB = TB ? 28 : 32;
    int st = 0;
    uint32_t ph = 0;
    int prev = 0;
    const uint64_t da0 = mkdesc(sb + wg * 8192, 16, 1024);
    const uint64_t db0 = TB ? mkdesc(sb + 16384, 8192, 1024) : mkdesc(sb + 16384, 16, 1024);
#pragma unroll 1
    for (int i = 0; i < NKB; i++) {
        mbar_wait(sb + BAR_F2 + 8 * st, ph);
        if (threadIdx.x == 0 && (i == 0 || i == 8 || i == 16 || i == 24 || i == 26 || i == 27)) TL(0, 14 + (i == 26 ? 4 : (i == 27 ? 5 : i / 8)));
        const uint64_t da = da0 + st * (SSZ / 16), db = db0 + st * (SSZ / 16);
        wg_arrive();
#pragma unroll
        for (int s = 0; s < 4; s++) wgmma_n224<TB>(acc, da + s * 2, db + s * (TB ? 128 : 2), i | s);
        wg_commit();
        wg_wait<1>();
        if (i > 0 && i <= NKB - NST && lane == 0) mbar_arrive_both(sb + BAR_E2 + 8 * prev);
        prev = st;
        if (++st == NST) { st = 0; ph ^= 1; }
    }
    wg_wait<0>();
}

struct Maps {
    CUtensorMap wg, wu, hre, him, h, h64, abT, abT_st, sre, sim, wd;
};
struct Ptrs {
    const __nv_bfloat16 *x, *hre, *him, *wg, *wu, *wd;
    __nv_bfloat16* out;
};
__device__ __forceinline__ void mbar_arrive(uint32_t b) {
    asm volatile("mbarrier.arrive.shared::cta.b64 _, [%0];" ::"r"(b) : "memory");
}
__device__ __forceinline__ void l2_prefetch(const void* p, uint32_t bytes) {
    asm volatile("cp.async.bulk.prefetch.L2.global [%0], %1;" ::"l"(p), "r"(bytes) : "memory");
}
__device__ __forceinline__ void tma_prefetch(const CUtensorMap* m, int c0, int c1) {
    asm volatile("cp.async.bulk.prefetch.tensor.2d.L2.global.tile [%0, {%1, %2}];" ::"l"(m), "r"(c0), "r"(c1) : "memory");
}

__device__ __forceinline__ void cnt_wait(uint32_t addr, uint32_t need) {
    uint32_t v;
    do { asm volatile("ld.acquire.cta.shared.u32 %0, [%1];" : "=r"(v) : "r"(addr) : "memory"); } while (v < need);
}
__device__ __forceinline__ void dep_wait(uint32_t sb, uint32_t need) { cnt_wait(sb + DEP_CNT, need); }

__global__ void __launch_bounds__(384, 1)
fused_kernel(const __grid_constant__ Ptrs pt, const __grid_constant__ Maps tm) {
    extern __shared__ unsigned char smem_raw[];
    const uint32_t sb = (s2u(smem_raw) + 1023) & ~1023u;
    const int tid = threadIdx.x, lane = tid & 31;
    const int warp = __shfl_sync(0xffffffffu, tid >> 5, 0);
    const int rank = blockIdx.x & 1;
    const int cid = blockIdx.x >> 1;
    const int j = cid & 7;
    const int rb = (cid >> 3) * 2 + rank;
    const int npass = n_passes(j);
    const int n = j & 1;
    const int part = j >> 1;

    {
        const int l8 = lane & 7, sub = lane >> 3;
        uint4 v[3][7];
#pragma unroll
        for (int it = 0; it < 3; it++) {
            const int qd = warp + 12 * it;
            if (qd < 32) {
                const uint4* src = reinterpret_cast<const uint4*>(pt.x + (size_t)(rb * 128 + qd * 4 + sub) * D_) + l8;
#pragma unroll
                for (int i = 0; i < 7; i++) v[it][i] = __ldg(src + i * 8);
            }
        }
        if (tid == 256) {
            TL(0, 0);
            for (int i = 0; i < S1_STAGES; i++) { mbar_init(sb + BAR_F1 + 8 * i, 1); mbar_init(sb + BAR_E1 + 8 * i, 8); }
            for (int i = 0; i < Y_STAGES; i++) { mbar_init(sb + BAR_F2 + 8 * i, 1); mbar_init(sb + BAR_E2 + 8 * i, 16); }
            mbar_init(sb + BAR_S1DONE, 16);
            mbar_init(sb + BAR_SF, 4);
            asm volatile("st.shared.u32 [%0], %1;" ::"r"(sb + SE_CNT), "r"(0) : "memory");
            asm volatile("st.shared.u32 [%0], %1;" ::"r"(sb + DEP_CNT), "r"(0) : "memory");
            asm volatile("fence.mbarrier_init.release.cluster;" ::: "memory");
        }
        __syncwarp();
        asm volatile("barrier.cluster.arrive.relaxed.aligned;\nbarrier.cluster.wait.aligned;" ::: "memory");
        if (tid == 256) {
            const int slab = pass_slab(j, 0);
            for (int kb = 0; kb < S1_STAGES; kb++) {
                const uint32_t dst = sb + S1_B + kb * 16384 + rank * 8192;
                const uint32_t fb = sb + BAR_F1 + 8 * kb;
                mbar_expect(fb, 16384);
                if (slab >= 0) {
                    tma_load_mc(dst, rank ? &tm.wu : &tm.wg, fb, slab * 64, kb * 64);
                } else {
                    const int a = 2 * j + rank;
                    tma_load_mc(dst, a < 7 ? &tm.hre : &tm.him, fb, kb * 64, (a < 7 ? a : a - 7) * 64);
                }
            }
            const int b = blockIdx.x;
            l2_prefetch((const char*)pt.hre + b * 3136, 3136);
            l2_prefetch((const char*)pt.him + b * 3136, 3136);
            l2_prefetch((const char*)pt.wg + b * 12544, 12544);
            l2_prefetch((const char*)pt.wu + b * 12544, 12544);
            l2_prefetch((const char*)pt.wd + b * 12544, 12544);
        }
        __syncwarp();
        if (tid == 0) TL(0, 1);
#pragma unroll
        for (int it = 0; it < 3; it++) {
            const int qd = warp + 12 * it;
            if (qd < 32) {
                const int row = qd * 4 + sub;
                float s0 = 0.f, s1 = 0.f, q0 = 0.f, q1 = 0.f;
#pragma unroll
                for (int i = 0; i < 7; i++) {
                    const uint32_t w[4] = {v[it][i].x, v[it][i].y, v[it][i].z, v[it][i].w};
#pragma unroll
                    for (int c = 0; c < 4; c++) {
                        const float d0 = bf_lo(w[c]), d1 = bf_hi(w[c]);
                        s0 += d0; s1 += d1;
                        q0 = fmaf(d0, d0, q0);
                        q1 = fmaf(d1, d1, q1);
                    }
                }
                float s = s0 + s1, q = q0 + q1;
#pragma unroll
                for (int o = 1; o < 8; o <<= 1) {
                    s += __shfl_xor_sync(0xffffffffu, s, o);
                    q += __shfl_xor_sync(0xffffffffu, q, o);
                }
                if (it == 0 && tid == 0) TL(0, 3);
                const float mean = s * (1.0f / D_);
                const float var = rbf(fmaxf(fmaf(-mean, mean, q * (1.0f / D_)), 0.f));
                const float den = rbf(sqrtf(rbf(var + 1e-5f)));
                const float rinv = 1.0f / den;
                const float rhi = rbf(rinv);
                const uint32_t m2 = pack_bf16(mean, mean), rhi2 = pack_bf16(rhi, rhi), rlo2 = pack_bf16(rinv - rhi, rinv - rhi);
                const uint32_t dst = sb + S1_XN + row * 128 + ((l8 ^ (row & 7)) << 4);
#pragma unroll
                for (int i = 0; i < 7; i++) {
                    const uint32_t w[4] = {v[it][i].x, v[it][i].y, v[it][i].z, v[it][i].w};
                    uint32_t o[4];
#pragma unroll
                    for (int c = 0; c < 4; c++) {
                        const uint32_t xc = hsub2(w[c], m2);
                        o[c] = hfma2(xc, rhi2, hmul2(xc, rlo2));
                    }
                    asm volatile("st.shared.v4.b32 [%0], {%1, %2, %3, %4};" ::"r"(dst + i * 16384), "r"(o[0]), "r"(o[1]), "r"(o[2]), "r"(o[3]) : "memory");
                }
            }
        }
        fence_async();
        __syncthreads();
        if (tid == 0) TL(0, 2);
    }

    if (warp >= 8) {
        asm volatile("setmaxnreg.dec.sync.aligned.u32 40;");
        if (warp == 8) {
            if (lane == 0) {
                int st = 0;
                uint32_t ph = 0;
                for (int p = 0; p < npass; p++) {
                    const int slab = pass_slab(j, p);
                    for (int kb = p ? 0 : S1_STAGES; kb < 7; kb++) {
                        mbar_wait(sb + BAR_E1 + 8 * st, ph);
                        const uint32_t dst = sb + S1_B + st * 16384 + rank * 8192;
                        const uint32_t fb = sb + BAR_F1 + 8 * st;
                        mbar_expect(fb, 16384);
                        if (slab >= 0) {
                            tma_load_mc(dst, rank ? &tm.wu : &tm.wg, fb, slab * 64, kb * 64);
                        } else {
                            const int a = 2 * j + rank;
                            tma_load_mc(dst, a < 7 ? &tm.hre : &tm.him, fb, kb * 64, (a < 7 ? a : a - 7) * 64);
                        }
                        if (++st == S1_STAGES) { st = 0; ph ^= 1; }
                        if (p == 1 && part < 2) {
                            for (int q = kb; q < 16; q += 7) tma_prefetch(part ? &tm.sim : &tm.sre, (2 * q + n) * 64, rb * 128);
                        }
                    }
                }
                if (part < 3) {
                    mbar_wait(sb + BAR_S1DONE, 0);
                    TL(0, 24);
                    st = 0; ph = 1;
                    if (part < 2) {
                        const CUtensorMap* ma = part ? &tm.sim : &tm.sre;
                        for (int g = 0; g < 32; g++) {
                            mbar_wait(sb + BAR_E2 + 8 * st, ph);
                            const uint32_t dst = sb + st * Y_STAGE;
                            const uint32_t fb = sb + BAR_F2 + 8 * st;
                            mbar_expect(fb, Y_STAGE);
                            tma_load(dst, ma, fb, g * 64, rb * 128);
                            dep_wait(sb, (g >> 1) + 1);
                            tma_load_mc(dst + 16384 + rank * 14336, &tm.abT, fb, g * 64, part * 448 + n * 224 + rank * 112);
                            if (++st == Y_STAGES) { st = 0; ph ^= 1; }
                        }
                    } else {
                        for (int g = 0; g < 28; g++) {
                            mbar_wait(sb + BAR_E2 + 8 * st, ph);
                            const uint32_t dst = sb + st * F_STAGE;
                            const uint32_t fb = sb + BAR_F2 + 8 * st;
                            mbar_expect(fb, F_STAGE);
                            tma_load_mc(dst + 16384 + (2 * rank) * 8192, &tm.wd, fb, n * 224 + (2 * rank) * 64, g * 64);
                            tma_load_mc(dst + 16384 + (2 * rank + 1) * 8192, &tm.wd, fb, n * 224 + (2 * rank + 1) * 64, g * 64);
                            dep_wait(sb, g + 1);
                            tma_load(dst, &tm.h, fb, g * 64, rb * 128);
                            if (++st == F_STAGES) { st = 0; ph ^= 1; }
                        }
                    }
                }
            }
        } else if (warp == 9) {
            if (part < 3) {
                const int ndep = part < 2 ? 16 : 29;
                const unsigned int epoch = *(volatile unsigned int*)&g_fl.done / gridDim.x + 1;
                const unsigned int* f = part < 2 ? &g_fl.ab[lane & 15] : (lane < 28 ? &g_fl.h[rb * 28 + lane] : &g_fl.y[rb * 2 + n]);
                const unsigned int target = (part < 2 ? 7 : (lane < 27 ? 1 : 2)) * epoch;
                bool ok = lane >= ndep;
                int published = 0;
                for (int spins = 0; published < ndep && spins < (1 << 22); spins++) {
                    if (!ok) {
                        unsigned int v;
                        asm volatile("ld.acquire.gpu.global.u32 %0, [%1];" : "=r"(v) : "l"(f) : "memory");
                        ok = (int)(v - target) >= 0;
                    }
                    const unsigned int m = __ballot_sync(0xffffffffu, ok);
                    const int cnt = min(__ffs(~m) - 1, ndep);
                    if (m == 0xffffffffu || cnt > published) {
                        published = (m == 0xffffffffu) ? ndep : cnt;
                        fence_async_all();
                        __syncwarp();
                        if (lane == 0) asm volatile("st.release.cta.shared.u32 [%0], %1;" ::"r"(sb + DEP_CNT), "r"(published) : "memory");
                    }
                }
                if (published < ndep && lane == 0)
                    asm volatile("st.release.cta.shared.u32 [%0], %1;" ::"r"(sb + DEP_CNT), "r"(ndep) : "memory");
            }
        } else if (warp == 10) {
            if (lane == 0) {
                for (int p = 0; p < npass; p++) {
                    const int slab = pass_slab(j, p);
                    mbar_wait(sb + BAR_SF, p & 1);
                    if (slab == 27) tma_store(&tm.h64, sb + STG, slab * 64, rb * 128 + n * 64);
                    else if (slab >= 0) tma_store(&tm.h, sb + STG, slab * 64, rb * 128);
                    else {
                        tma_store(&tm.abT_st, sb + S1_B, rb * 128 + 64, j * 128);
                        bulk_commit();
                        tma_store(&tm.abT_st, sb + STG, rb * 128, j * 128);
                    }
                    bulk_commit();
                    if (slab < 0) {
                        asm volatile("cp.async.bulk.wait_group.read 1;" ::: "memory");
                        for (int w = 0; w < 4; w++) mbar_arrive_both(sb + BAR_E1);
                    }
                    bulk_wait_read0();
                    asm volatile("st.release.cta.shared.u32 [%0], %1;" ::"r"(sb + SE_CNT), "r"(p + 1) : "memory");
                    bulk_wait0();
                    fence_async_all();
                    flag_add(slab >= 0 ? &g_fl.h[rb * 28 + slab] : &g_fl.ab[rb]);
                }
            }
        }
        __syncwarp();
    } else {
        asm volatile("setmaxnreg.inc.sync.aligned.u32 232;");
        const int wg = warp >> 2, wl = warp & 3, wtid = tid & 127;
        const int qd = lane & 3;
        {
            float acc[2][64];
            for (int p = wg; p < npass; p += 2) {
                const int slab = pass_slab(j, p);
                if (p > 0) bar_sync(4 + (p & 1), 256);
                const int handoff = (p + 1 < npass) ? 4 + ((p + 1) & 1) : 0;
                if (slab == 27) s1_mainloop<2>(acc, sb, p, lane, handoff, n);
                else if (slab >= 0) s1_mainloop<1>(acc, sb, p, lane, handoff);
                else s1_mainloop<0>(acc, sb, p, lane, handoff);
                if (p + 2 >= npass && part < 3 && lane == 0) mbar_arrive_both(sb + BAR_S1DONE);
                if (wtid == 0 && p < 4) TL(0, 4 + p);

                const uint32_t srow = sb + STG + (wl * 16 + (lane & 7) + ((lane >> 3) & 1) * 8) * 128;
                if (slab >= 0) {
                    uint32_t hv[2][16];
#pragma unroll
                    for (int mh = 0; mh < 2; mh++) {
                        if (mh == 0 || slab != 27) {
#pragma unroll
                            for (int i = 0; i < 16; i++) {
                                const uint32_t g2 = pack_bf16(acc[mh][2 * i], acc[mh][2 * i + 1]);
                                const uint32_t u2 = pack_bf16(acc[mh][32 + 2 * i], acc[mh][32 + 2 * i + 1]);
                                const uint32_t a2 = pack_bf16(gelu_tanh(bf_lo(g2)), gelu_tanh(bf_hi(g2)));
                                hv[mh][i] = hmul2(a2, u2);
                            }
                        }
                    }
                    cnt_wait(sb + SE_CNT, p);
#pragma unroll
                    for (int mh = 0; mh < 2; mh++) {
                        if (mh == 0 || slab != 27) {
#pragma unroll
                            for (int jj = 0; jj < 8; jj += 2)
                                stmat4(srow + mh * 8192 + (((jj + (lane >> 4)) ^ (lane & 7)) << 4),
                                       hv[mh][2 * jj], hv[mh][2 * jj + 1], hv[mh][2 * jj + 2], hv[mh][2 * jj + 3]);
                        }
                    }
                } else {
                    bar_sync(2, 128);
#pragma unroll
                    for (int hf = 0; hf < 2; hf++) {
#pragma unroll
                        for (int mh = 0; mh < 2; mh++) {
#pragma unroll
                            for (int jj = 0; jj < 8; jj += 2) {
                                const int o = hf * 32 + jj * 4;
                                stmat4(srow - hf * (STG - S1_B) + mh * 8192 + (((jj + (lane >> 4)) ^ (lane & 7)) << 4),
                                       pack_bf16(acc[mh][o], acc[mh][o + 1]), pack_bf16(acc[mh][o + 2], acc[mh][o + 3]),
                                       pack_bf16(acc[mh][o + 4], acc[mh][o + 5]), pack_bf16(acc[mh][o + 6], acc[mh][o + 7]));
                            }
                        }
                    }
                }
                fence_async();
                __syncwarp();
                if (lane == 0) mbar_arrive(sb + BAR_SF);
                if (wtid == 0 && p < 4) TL(0, 10 + p);
            }
        }
        if (wtid == 0) TL(0, 20 + wg);
        if (part < 3) {
            {
                float acc[112];
                const size_t base = (size_t)(rb * 128 + wg * 64 + wl * 16 + (lane >> 2)) * D_ + n * 224 + qd * 8;
                if (part < 2) {
                    s2_mainloop<0>(acc, sb, wg, lane);
                    if (tid == 0) TL(0, 25);
                    bar_sync(1, 256);
#pragma unroll
                    for (int i = 0; i < 14; i++)
                        asm volatile("st.shared.v4.b32 [%0], {%1, %2, %3, %4};" ::"r"(sb + (i * 256 + tid) * 16),
                                     "r"(pack_bf16(acc[8 * i], acc[8 * i + 1])), "r"(pack_bf16(acc[8 * i + 2], acc[8 * i + 3])),
                                     "r"(pack_bf16(acc[8 * i + 4], acc[8 * i + 5])), "r"(pack_bf16(acc[8 * i + 6], acc[8 * i + 7])) : "memory");
                    fence_async();
                    bar_sync(1, 256);
                    if (tid == 0) {
                        uint4* dst = g_y + (size_t)((part * 32 + rb * 2 + n) * 14) * 256;
                        asm volatile("cp.async.bulk.global.shared::cta.bulk_group [%0], [%1], %2;" ::"l"(dst), "r"(sb), "r"(14 * 256 * 16) : "memory");
                        bulk_commit();
                        bulk_wait0();
                        fence_async_all();
                        flag_add(&g_fl.y[rb * 2 + n]);
                    }
                } else {
                    uint4 xv[14];
#pragma unroll
                    for (int i = 0; i < 14; i++)
                        xv[i] = __ldg(reinterpret_cast<const uint4*>(pt.x + base + (i / 7) * 8 * D_ + (i % 7) * 32));
                    s2_mainloop<1>(acc, sb, wg, lane);
                    if (tid == 0) TL(0, 25);
                    dep_wait(sb, 29);
                    if (tid == 0) TL(0, 26);
                    const uint4* ysrc = g_y + (size_t)((rb * 2 + n) * 14) * 256 + tid;
                    uint4 yr[14], yi[14];
#pragma unroll
                    for (int i = 0; i < 14; i++) yr[i] = __ldcg(ysrc + i * 256);
                    uint32_t sg[56];
#pragma unroll
                    for (int i = 0; i < 56; i++) {
                        const uint32_t f2 = pack_bf16(acc[2 * i], acc[2 * i + 1]);
                        sg[i] = pack_bf16(silu(bf_lo(f2)), silu(bf_hi(f2)));
                    }
#pragma unroll
                    for (int i = 0; i < 14; i++) yi[i] = __ldcg(ysrc + (32 * 14 + i) * 256);
#pragma unroll
                    for (int i = 0; i < 14; i++) {
                        sg[4 * i + 0] = hmul2(hsub2(yr[i].x, yi[i].x), sg[4 * i + 0]);
                        sg[4 * i + 1] = hmul2(hsub2(yr[i].y, yi[i].y), sg[4 * i + 1]);
                        sg[4 * i + 2] = hmul2(hsub2(yr[i].z, yi[i].z), sg[4 * i + 2]);
                        sg[4 * i + 3] = hmul2(hsub2(yr[i].w, yi[i].w), sg[4 * i + 3]);
                    }
#pragma unroll
                    for (int hh = 0; hh < 2; hh++) {
#pragma unroll
                        for (int g4 = 0; g4 < 7; g4++) {
                            uint32_t r[4];
#pragma unroll
                            for (int t = 0; t < 4; t++) r[t] = sg[(g4 * 4 + t) * 2 + hh];
                            quad_transpose(r, qd);
                            const uint4 xx = xv[hh * 7 + g4];
                            *reinterpret_cast<uint4*>(pt.out + base + hh * 8 * D_ + g4 * 32) =
                                make_uint4(hadd2(xx.x, r[0]), hadd2(xx.y, r[1]), hadd2(xx.z, r[2]), hadd2(xx.w, r[3]));
                        }
                    }
                }
            }
        }
    }
    if (tid == 0) TL(0, 29);
    __syncthreads();
    if (tid == 0) {
        TL(0, 30);
        atomicAdd(&g_fl.done, 1u);
    }
}

typedef CUresult (*EncFn)(CUtensorMap*, CUtensorMapDataType, cuuint32_t, void*, const cuuint64_t*, const cuuint64_t*,
                          const cuuint32_t*, const cuuint32_t*, CUtensorMapInterleave, CUtensorMapSwizzle,
                          CUtensorMapL2promotion, CUtensorMapFloatOOBfill);

void make_map(EncFn enc, CUtensorMap* m, const void* ptr, int rows, int cols, int box_rows, int box_cols, int pitch = 0) {
    const bool swz = true;
    cuuint64_t gd[2] = {(cuuint64_t)cols, (cuuint64_t)rows};
    cuuint64_t gs[1] = {(cuuint64_t)(pitch ? pitch : cols) * 2};
    cuuint32_t bx[2] = {(cuuint32_t)box_cols, (cuuint32_t)box_rows};
    cuuint32_t es[2] = {1, 1};
    enc(m, CU_TENSOR_MAP_DATA_TYPE_BFLOAT16, 2, const_cast<void*>(ptr), gd, gs, bx, es, CU_TENSOR_MAP_INTERLEAVE_NONE,
        swz ? CU_TENSOR_MAP_SWIZZLE_128B : CU_TENSOR_MAP_SWIZZLE_NONE, CU_TENSOR_MAP_L2_PROMOTION_L2_128B,
        CU_TENSOR_MAP_FLOAT_OOB_FILL_NONE);
}

}

extern "C" void kernel_launch(void* const* d_in, const int* in_sizes, int n_in, void* d_out, int out_size) {
    Ptrs pt;
    pt.x = (const __nv_bfloat16*)d_in[0];
    pt.hre = (const __nv_bfloat16*)d_in[3];
    pt.him = (const __nv_bfloat16*)d_in[4];
    pt.wg = (const __nv_bfloat16*)d_in[6];
    pt.wu = (const __nv_bfloat16*)d_in[7];
    pt.wd = (const __nv_bfloat16*)d_in[8];
    pt.out = (__nv_bfloat16*)d_out;

    void* fn = nullptr;
    cudaDriverEntryPointQueryResult qr;
    cudaGetDriverEntryPoint("cuTensorMapEncodeTiled", &fn, cudaEnableDefault, &qr);
    EncFn enc = (EncFn)fn;
    void *p_abT, *p_h;
    cudaGetSymbolAddress(&p_abT, g_abT);
    cudaGetSymbolAddress(&p_h, g_h);

    Maps tm;
    make_map(enc, &tm.wg, d_in[6], D_, F_, 64, 64);
    make_map(enc, &tm.wu, d_in[7], D_, F_, 64, 64);
    make_map(enc, &tm.hre, d_in[3], D_, D_, 64, 64);
    make_map(enc, &tm.him, d_in[4], D_, D_, 64, 64);
    make_map(enc, &tm.h, p_h, S_, F_, 128, 64);
    make_map(enc, &tm.h64, p_h, S_, F_, 64, 64);
    make_map(enc, &tm.abT, p_abT, 896, S_, 112, 64, ABP);
    make_map(enc, &tm.abT_st, p_abT, 896, S_, 128, 64, ABP);
    make_map(enc, &tm.sre, d_in[1], S_, S_, 128, 64);
    make_map(enc, &tm.sim, d_in[2], S_, S_, 128, 64);
    make_map(enc, &tm.wd, d_in[8], F_, D_, 64, 64);

    cudaFuncSetAttribute(fused_kernel, cudaFuncAttributeMaxDynamicSharedMemorySize, SMEM_BYTES);

    cudaLaunchAttribute at[1];
    at[0].id = cudaLaunchAttributeClusterDimension;
    at[0].val.clusterDim.x = 2; at[0].val.clusterDim.y = 1; at[0].val.clusterDim.z = 1;
    cudaLaunchConfig_t cfg = {};
    cfg.gridDim = dim3(128); cfg.blockDim = dim3(384); cfg.stream = cudaStreamPerThread;
    cfg.attrs = at; cfg.numAttrs = 1;
    cfg.dynamicSmemBytes = SMEM_BYTES;
    cudaLaunchKernelEx(&cfg, fused_kernel, pt, tm);
}
```

```cpp
#include <cuda_runtime.h>
#include <cuda_bf16.h>
#include <cuda.h>
#include <stdint.h>

namespace {

constexpr int S_ = 2048, D_ = 448, F_ = 1792;

constexpr int ABP = 2048 + 64;
__device__ __align__(1024) __nv_bfloat16 g_abT[896 * ABP];
__device__ __align__(1024) __nv_bfloat16 g_h[2048 * 1792];
__device__ __align__(1024) uint4 g_y[2 * 32 * 14 * 256];
struct Flags {
    unsigned int ab[16];
    unsigned int h[16 * 28];
    unsigned int y[32];
    unsigned int done;
};
__device__ Flags g_fl;

__device__ __forceinline__ uint32_t s2u(const void* p) { return (uint32_t)__cvta_generic_to_shared(p); }
__device__ __forceinline__ void mbar_init(uint32_t b, int c) {
    asm volatile("mbarrier.init.shared::cta.b64 [%0], %1;" ::"r"(b), "r"(c));
}
__device__ __forceinline__ void mbar_expect(uint32_t b, uint32_t bytes) {
    asm volatile("mbarrier.arrive.expect_tx.shared::cta.b64 _, [%0], %1;" ::"r"(b), "r"(bytes) : "memory");
}
__device__ __forceinline__ void mbar_wait(uint32_t b, uint32_t ph) {
    uint32_t ok;
    do {
        asm volatile("{\n.reg .pred p;\nmbarrier.try_wait.parity.shared::cta.b64 p, [%1], %2;\nselp.u32 %0, 1, 0, p;\n}"
                     : "=r"(ok) : "r"(b), "r"(ph) : "memory");
    } while (!ok);
}
__device__ __forceinline__ void mbar_arrive_both(uint32_t b) {
    asm volatile("{\n.reg .b32 r0, r1;\n"
                 "mapa.shared::cluster.u32 r0, %0, 0;\n"
                 "mapa.shared::cluster.u32 r1, %0, 1;\n"
                 "mbarrier.arrive.shared::cluster.b64 _, [r0];\n"
                 "mbarrier.arrive.shared::cluster.b64 _, [r1];\n}"
                 ::"r"(b) : "memory");
}
__device__ __forceinline__ void tma_load(uint32_t dst, const CUtensorMap* m, uint32_t bar, int c0, int c1) {
    asm volatile("cp.async.bulk.tensor.2d.shared::cluster.global.mbarrier::complete_tx::bytes [%0], [%1, {%3, %4}], [%2];"
                 ::"r"(dst), "l"(m), "r"(bar), "r"(c0), "r"(c1) : "memory");
}
__device__ __forceinline__ void tma_load_mc(uint32_t dst, const CUtensorMap* m, uint32_t bar, int c0, int c1) {
    asm volatile("cp.async.bulk.tensor.2d.shared::cluster.global.mbarrier::complete_tx::bytes.multicast::cluster [%0], [%1, {%3, %4}], [%2], %5;"
                 ::"r"(dst), "l"(m), "r"(bar), "r"(c0), "r"(c1), "h"((uint16_t)3) : "memory");
}
__device__ __forceinline__ void tma_store(const CUtensorMap* m, uint32_t src, int c0, int c1) {
    asm volatile("cp.async.bulk.tensor.2d.global.shared::cta.bulk_group [%0, {%2, %3}], [%1];"
                 ::"l"(m), "r"(src), "r"(c0), "r"(c1) : "memory");
}
__device__ __forceinline__ void bulk_commit() { asm volatile("cp.async.bulk.commit_group;" ::: "memory"); }
__device__ __forceinline__ void bulk_wait_read0() { asm volatile("cp.async.bulk.wait_group.read 0;" ::: "memory"); }
__device__ __forceinline__ void bulk_wait0() { asm volatile("cp.async.bulk.wait_group 0;" ::: "memory"); }
__device__ __forceinline__ void fence_async() { asm volatile("fence.proxy.async.shared::cta;" ::: "memory"); }
__device__ __forceinline__ void fence_async_all() { asm volatile("fence.proxy.async;" ::: "memory"); }
__device__ __forceinline__ void bar_sync(int id, int n) { asm volatile("bar.sync %0, %1;" ::"r"(id), "r"(n) : "memory"); }
__device__ __forceinline__ void wg_arrive() { asm volatile("wgmma.fence.sync.aligned;" ::: "memory"); }
__device__ __forceinline__ void wg_commit() { asm volatile("wgmma.commit_group.sync.aligned;" ::: "memory"); }
template <int N> __device__ __forceinline__ void wg_wait() { asm volatile("wgmma.wait_group.sync.aligned %0;" ::"n"(N) : "memory"); }
__device__ __forceinline__ void stmat4(uint32_t a, uint32_t r0, uint32_t r1, uint32_t r2, uint32_t r3) {
    asm volatile("stmatrix.sync.aligned.m8n8.x4.shared.b16 [%0], {%1, %2, %3, %4};" ::"r"(a), "r"(r0), "r"(r1), "r"(r2), "r"(r3) : "memory");
}
__device__ __forceinline__ void flag_add(unsigned int* f) {
    asm volatile("red.release.gpu.global.add.u32 [%0], 1;" ::"l"(f) : "memory");
}
__device__ __forceinline__ void quad_transpose(uint32_t (&r)[4], int q) {
    const bool o1 = q & 1, o2 = q & 2;
    uint32_t a = o1 ? r[0] : r[1], b = o1 ? r[2] : r[3];
    a = __shfl_xor_sync(0xffffffffu, a, 1);
    b = __shfl_xor_sync(0xffffffffu, b, 1);
    if (o1) { r[0] = a; r[2] = b; } else { r[1] = a; r[3] = b; }
    a = o2 ? r[0] : r[2]; b = o2 ? r[1] : r[3];
    a = __shfl_xor_sync(0xffffffffu, a, 2);
    b = __shfl_xor_sync(0xffffffffu, b, 2);
    if (o2) { r[0] = a; r[1] = b; } else { r[2] = a; r[3] = b; }
}
__device__ __forceinline__ uint64_t mkdesc(uint32_t addr, uint32_t lbo, uint32_t sbo) {
    return (uint64_t)((addr & 0x3FFFF) >> 4) | ((uint64_t)(lbo >> 4) << 16) | ((uint64_t)(sbo >> 4) << 32) | (1ull << 62);
}
__device__ __forceinline__ uint32_t pack_bf16(float lo, float hi) {
    uint32_t r;
    asm("cvt.rn.bf16x2.f32 %0, %1, %2;" : "=r"(r) : "f"(hi), "f"(lo));
    return r;
}
__device__ __forceinline__ uint32_t hsub2(uint32_t a, uint32_t b) { uint32_t r; asm("sub.rn.bf16x2 %0, %1, %2;" : "=r"(r) : "r"(a), "r"(b)); return r; }
__device__ __forceinline__ uint32_t hadd2(uint32_t a, uint32_t b) { uint32_t r; asm("add.rn.bf16x2 %0, %1, %2;" : "=r"(r) : "r"(a), "r"(b)); return r; }
__device__ __forceinline__ uint32_t hmul2(uint32_t a, uint32_t b) { uint32_t r; asm("mul.rn.bf16x2 %0, %1, %2;" : "=r"(r) : "r"(a), "r"(b)); return r; }
__device__ __forceinline__ uint32_t hfma2(uint32_t a, uint32_t b, uint32_t c) { uint32_t r; asm("fma.rn.bf16x2 %0, %1, %2, %3;" : "=r"(r) : "r"(a), "r"(b), "r"(c)); return r; }
__device__ __forceinline__ float bf_lo(uint32_t u) { return __uint_as_float(u << 16); }
__device__ __forceinline__ float bf_hi(uint32_t u) { return __uint_as_float(u & 0xffff0000u); }
__device__ __forceinline__ float rbf(float v) { return __bfloat162float(__float2bfloat16_rn(v)); }
__device__ __forceinline__ float tanh_fast(float x) { float r; asm("tanh.approx.f32 %0, %1;" : "=f"(r) : "f"(x)); return r; }
__device__ __forceinline__ float gelu_tanh(float x) {
    float u = x * fmaf(x * x, 0.0356774081f, 0.7978845608f);
    float hx = 0.5f * x;
    return fmaf(hx, tanh_fast(u), hx);
}
__device__ __forceinline__ float silu(float f) { const float hf = 0.5f * f; return fmaf(hf, tanh_fast(hf), hf); }

template <int TB>
__device__ __forceinline__ void wgmma_n128(float (&d)[64], uint64_t da, uint64_t db, int scaleD) {
    asm volatile("{\n.reg .pred p;\nsetp.ne.b32 p, %66, 0;\n"
        "wgmma.mma_async.sync.aligned.m64n128k16.f32.bf16.bf16 {%0, %1, %2, %3, %4, %5, %6, %7, %8, %9, %10, %11, %12, %13, %14, %15, %16, %17, %18, %19, %20, %21, %22, %23, %24, %25, %26, %27, %28, %29, %30, %31, %32, %33, %34, %35, %36, %37, %38, %39, %40, %41, %42, %43, %44, %45, %46, %47, %48, %49, %50, %51, %52, %53, %54, %55, %56, %57, %58, %59, %60, %61, %62, %63}, %64, %65, p, 1, 1, 0, %67;\n}\n"
        : "+f"(d[0]), "+f"(d[1]), "+f"(d[2]), "+f"(d[3]), "+f"(d[4]), "+f"(d[5]), "+f"(d[6]), "+f"(d[7]), "+f"(d[8]), "+f"(d[9]), "+f"(d[10]), "+f"(d[11]), "+f"(d[12]), "+f"(d[13]), "+f"(d[14]), "+f"(d[15]), "+f"(d[16]), "+f"(d[17]), "+f"(d[18]), "+f"(d[19]), "+f"(d[20]), "+f"(d[21]), "+f"(d[22]), "+f"(d[23]), "+f"(d[24]), "+f"(d[25]), "+f"(d[26]), "+f"(d[27]), "+f"(d[28]), "+f"(d[29]), "+f"(d[30]), "+f"(d[31]), "+f"(d[32]), "+f"(d[33]), "+f"(d[34]), "+f"(d[35]), "+f"(d[36]), "+f"(d[37]), "+f"(d[38]), "+f"(d[39]), "+f"(d[40]), "+f"(d[41]), "+f"(d[42]), "+f"(d[43]), "+f"(d[44]), "+f"(d[45]), "+f"(d[46]), "+f"(d[47]), "+f"(d[48]), "+f"(d[49]), "+f"(d[50]), "+f"(d[51]), "+f"(d[52]), "+f"(d[53]), "+f"(d[54]), "+f"(d[55]), "+f"(d[56]), "+f"(d[57]), "+f"(d[58]), "+f"(d[59]), "+f"(d[60]), "+f"(d[61]), "+f"(d[62]), "+f"(d[63])
        : "l"(da), "l"(db), "r"(scaleD), "n"(TB));
}
template <int TB>
__device__ __forceinline__ void wgmma_n224(float (&d)[112], uint64_t da, uint64_t db, int scaleD) {
    asm volatile("{\n.reg .pred p;\nsetp.ne.b32 p, %114, 0;\n"
        "wgmma.mma_async.sync.aligned.m64n224k16.f32.bf16.bf16 {%0, %1, %2, %3, %4, %5, %6, %7, %8, %9, %10, %11, %12, %13, %14, %15, %16, %17, %18, %19, %20, %21, %22, %23, %24, %25, %26, %27, %28, %29, %30, %31, %32, %33, %34, %35, %36, %37, %38, %39, %40, %41, %42, %43, %44, %45, %46, %47, %48, %49, %50, %51, %52, %53, %54, %55, %56, %57, %58, %59, %60, %61, %62, %63, %64, %65, %66, %67, %68, %69, %70, %71, %72, %73, %74, %75, %76, %77, %78, %79, %80, %81, %82, %83, %84, %85, %86, %87, %88, %89, %90, %91, %92, %93, %94, %95, %96, %97, %98, %99, %100, %101, %102, %103, %104, %105, %106, %107, %108, %109, %110, %111}, %112, %113, p, 1, 1, 0, %115;\n}\n"
        : "+f"(d[0]), "+f"(d[1]), "+f"(d[2]), "+f"(d[3]), "+f"(d[4]), "+f"(d[5]), "+f"(d[6]), "+f"(d[7]), "+f"(d[8]), "+f"(d[9]), "+f"(d[10]), "+f"(d[11]), "+f"(d[12]), "+f"(d[13]), "+f"(d[14]), "+f"(d[15]), "+f"(d[16]), "+f"(d[17]), "+f"(d[18]), "+f"(d[19]), "+f"(d[20]), "+f"(d[21]), "+f"(d[22]), "+f"(d[23]), "+f"(d[24]), "+f"(d[25]), "+f"(d[26]), "+f"(d[27]), "+f"(d[28]), "+f"(d[29]), "+f"(d[30]), "+f"(d[31]), "+f"(d[32]), "+f"(d[33]), "+f"(d[34]), "+f"(d[35]), "+f"(d[36]), "+f"(d[37]), "+f"(d[38]), "+f"(d[39]), "+f"(d[40]), "+f"(d[41]), "+f"(d[42]), "+f"(d[43]), "+f"(d[44]), "+f"(d[45]), "+f"(d[46]), "+f"(d[47]), "+f"(d[48]), "+f"(d[49]), "+f"(d[50]), "+f"(d[51]), "+f"(d[52]), "+f"(d[53]), "+f"(d[54]), "+f"(d[55]), "+f"(d[56]), "+f"(d[57]), "+f"(d[58]), "+f"(d[59]), "+f"(d[60]), "+f"(d[61]), "+f"(d[62]), "+f"(d[63]), "+f"(d[64]), "+f"(d[65]), "+f"(d[66]), "+f"(d[67]), "+f"(d[68]), "+f"(d[69]), "+f"(d[70]), "+f"(d[71]), "+f"(d[72]), "+f"(d[73]), "+f"(d[74]), "+f"(d[75]), "+f"(d[76]), "+f"(d[77]), "+f"(d[78]), "+f"(d[79]), "+f"(d[80]), "+f"(d[81]), "+f"(d[82]), "+f"(d[83]), "+f"(d[84]), "+f"(d[85]), "+f"(d[86]), "+f"(d[87]), "+f"(d[88]), "+f"(d[89]), "+f"(d[90]), "+f"(d[91]), "+f"(d[92]), "+f"(d[93]), "+f"(d[94]), "+f"(d[95]), "+f"(d[96]), "+f"(d[97]), "+f"(d[98]), "+f"(d[99]), "+f"(d[100]), "+f"(d[101]), "+f"(d[102]), "+f"(d[103]), "+f"(d[104]), "+f"(d[105]), "+f"(d[106]), "+f"(d[107]), "+f"(d[108]), "+f"(d[109]), "+f"(d[110]), "+f"(d[111])
        : "l"(da), "l"(db), "r"(scaleD), "n"(TB));
}


constexpr int S1_STAGES = 6;
constexpr int S1_XN = 0;
constexpr int S1_B = 7 * 16384;
constexpr int STG = S1_B + S1_STAGES * 16384;
constexpr int Y_STAGES = 4, Y_STAGE = 45056;
constexpr int F_STAGES = 4, F_STAGE = 49152;
constexpr int BAR = STG + 16384;
constexpr int BAR_F1 = BAR, BAR_E1 = BAR + 56, BAR_F2 = BAR + 112, BAR_E2 = BAR + 152, BAR_S1DONE = BAR + 192;
constexpr int BAR_SF = BAR + 208;
constexpr int SE_CNT = BAR + 216;
constexpr int DEP_CNT = BAR + 200;
constexpr int SMEM_BYTES = BAR + 256 + 1024;

__device__ __forceinline__ int n_passes(int j) { return j < 4 ? 2 : (j < 6 ? 4 : 10); }
__device__ __forceinline__ int pass_slab(int j, int p) {
    if (p == 0) return j < 7 ? -1 : 0;
    if (p == 1) return 1 + j;
    if (p < 4) return 4 * p - 3 + j;
    if (p == 9) return 27;
    return 17 + 2 * (p - 4) + (j - 6);
}

template <int TB>
__device__ __forceinline__ void s1_mainloop(float (&acc)[2][64], uint32_t sb, int p, int lane, int handoff, int half = 0) {
    int st = (p * 7) % S1_STAGES;
    uint32_t ph = ((p * 7) / S1_STAGES) & 1;
    int prev = 0;
    uint64_t dx = mkdesc(sb + S1_XN + half * 8192, 16, 1024);
    const uint64_t dw0 = TB ? mkdesc(sb + S1_B, 8192, 1024) : mkdesc(sb + S1_B, 16, 1024);
    const int nrel = lane == 0 ? (handoff ? 7 : 7 - S1_STAGES) : 0;
#pragma unroll 1
    for (int kb = 0; kb < 7; kb++) {
        mbar_wait(sb + BAR_F1 + 8 * st, ph);
        if (kb == 6 && handoff) asm volatile("bar.arrive %0, 256;" ::"r"(handoff) : "memory");
        const uint64_t dw = dw0 + st * 1024;
        wg_arrive();
#pragma unroll
        for (int s = 0; s < 4; s++) {
            if (TB == 2) {
                wgmma_n128<1>(acc[0], dx + s * 2, dw + s * 128, kb | s);
            } else if (TB) {
                wgmma_n128<1>(acc[0], dx + s * 2, dw + s * 128, kb | s);
                wgmma_n128<1>(acc[1], dx + 512 + s * 2, dw + s * 128, kb | s);
            } else {
                wgmma_n128<0>(acc[0], dw + s * 2, dx + s * 2, kb | s);
                wgmma_n128<0>(acc[1], dw + 512 + s * 2, dx + s * 2, kb | s);
            }
        }
        wg_commit();
        wg_wait<1>();
        if (kb > 0 && kb <= nrel) mbar_arrive_both(sb + BAR_E1 + 8 * prev);
        prev = st;
        dx += 1024;
        if (++st == S1_STAGES) { st = 0; ph ^= 1; }
    }
    wg_wait<0>();
    if (TB && nrel == 7) mbar_arrive_both(sb + BAR_E1 + 8 * prev);
}

template <int TB>
__device__ __forceinline__ void s2_mainloop(float (&acc)[112], uint32_t sb, int wg, int lane) {
    constexpr int NST = TB ? F_STAGES : Y_STAGES, SSZ = TB ? F_STAGE : Y_STAGE, NKB = TB ? 28 : 32;
    int st = 0;
    uint32_t ph = 0;
    int prev = 0;
    const uint64_t da0 = mkdesc(sb + wg * 8192, 16, 1024);
    const uint64_t db0 = TB ? mkdesc(sb + 16384, 8192, 1024) : mkdesc(sb + 16384, 16, 1024);
#pragma unroll 1
    for (int i = 0; i < NKB; i++) {
        mbar_wait(sb + BAR_F2 + 8 * st, ph);
        const uint64_t da = da0 + st * (SSZ / 16), db = db0 + st * (SSZ / 16);
        wg_arrive();
#pragma unroll
        for (int s = 0; s < 4; s++) wgmma_n224<TB>(acc, da + s * 2, db + s * (TB ? 128 : 2), i | s);
        wg_commit();
        wg_wait<1>();
        if (i > 0 && i <= NKB - NST && lane == 0) mbar_arrive_both(sb + BAR_E2 + 8 * prev);
        prev = st;
        if (++st == NST) { st = 0; ph ^= 1; }
    }
    wg_wait<0>();
}

struct Maps {
    CUtensorMap wg, wu, hre, him, h, h64, abT, abT_st, sre, sim, wd;
};
struct Ptrs {
    const __nv_bfloat16 *x, *hre, *him, *wg, *wu, *wd;
    __nv_bfloat16* out;
};
__device__ __forceinline__ void mbar_arrive(uint32_t b) {
    asm volatile("mbarrier.arrive.shared::cta.b64 _, [%0];" ::"r"(b) : "memory");
}
__device__ __forceinline__ void l2_prefetch(const void* p, uint32_t bytes) {
    asm volatile("cp.async.bulk.prefetch.L2.global [%0], %1;" ::"l"(p), "r"(bytes) : "memory");
}
__device__ __forceinline__ void tma_prefetch(const CUtensorMap* m, int c0, int c1) {
    asm volatile("cp.async.bulk.prefetch.tensor.2d.L2.global.tile [%0, {%1, %2}];" ::"l"(m), "r"(c0), "r"(c1) : "memory");
}

__device__ __forceinline__ void cnt_wait(uint32_t addr, uint32_t need) {
    uint32_t v;
    do { asm volatile("ld.acquire.cta.shared.u32 %0, [%1];" : "=r"(v) : "r"(addr) : "memory"); } while (v < need);
}
__device__ __forceinline__ void dep_wait(uint32_t sb, uint32_t need) { cnt_wait(sb + DEP_CNT, need); }

__global__ void __launch_bounds__(384, 1)
fused_kernel(const __grid_constant__ Ptrs pt, const __grid_constant__ Maps tm) {
    extern __shared__ unsigned char smem_raw[];
    const uint32_t sb = (s2u(smem_raw) + 1023) & ~1023u;
    const int tid = threadIdx.x, lane = tid & 31;
    const int warp = __shfl_sync(0xffffffffu, tid >> 5, 0);
    const int rank = blockIdx.x & 1;
    const int cid = blockIdx.x >> 1;
    const int j = cid & 7;
    const int rb = (cid >> 3) * 2 + rank;
    const int npass = n_passes(j);
    const int n = j & 1;
    const int part = j >> 1;

    {
        const int l8 = lane & 7, sub = lane >> 3;
        uint4 v[3][7];
#pragma unroll
        for (int it = 0; it < 3; it++) {
            const int qd = warp + 12 * it;
            if (qd < 32) {
                const uint4* src = reinterpret_cast<const uint4*>(pt.x + (size_t)(rb * 128 + qd * 4 + sub) * D_) + l8;
#pragma unroll
                for (int i = 0; i < 7; i++) v[it][i] = __ldg(src + i * 8);
            }
        }
        if (tid == 256) {
            for (int i = 0; i < S1_STAGES; i++) { mbar_init(sb + BAR_F1 + 8 * i, 1); mbar_init(sb + BAR_E1 + 8 * i, 8); }
            for (int i = 0; i < Y_STAGES; i++) { mbar_init(sb + BAR_F2 + 8 * i, 1); mbar_init(sb + BAR_E2 + 8 * i, 16); }
            mbar_init(sb + BAR_S1DONE, 16);
            mbar_init(sb + BAR_SF, 4);
            asm volatile("st.shared.u32 [%0], %1;" ::"r"(sb + SE_CNT), "r"(0) : "memory");
            asm volatile("st.shared.u32 [%0], %1;" ::"r"(sb + DEP_CNT), "r"(0) : "memory");
            asm volatile("fence.mbarrier_init.release.cluster;" ::: "memory");
        }
        __syncwarp();
        asm volatile("barrier.cluster.arrive.relaxed.aligned;\nbarrier.cluster.wait.aligned;" ::: "memory");
        if (tid == 256) {
            const int slab = pass_slab(j, 0);
            for (int kb = 0; kb < S1_STAGES; kb++) {
                const uint32_t dst = sb + S1_B + kb * 16384 + rank * 8192;
                const uint32_t fb = sb + BAR_F1 + 8 * kb;
                mbar_expect(fb, 16384);
                if (slab >= 0) {
                    tma_load_mc(dst, rank ? &tm.wu : &tm.wg, fb, slab * 64, kb * 64);
                } else {
                    const int a = 2 * j + rank;
                    tma_load_mc(dst, a < 7 ? &tm.hre : &tm.him, fb, kb * 64, (a < 7 ? a : a - 7) * 64);
                }
            }
            const int b = blockIdx.x;
            l2_prefetch((const char*)pt.hre + b * 3136, 3136);
            l2_prefetch((const char*)pt.him + b * 3136, 3136);
            l2_prefetch((const char*)pt.wg + b * 12544, 12544);
            l2_prefetch((const char*)pt.wu + b * 12544, 12544);
            l2_prefetch((const char*)pt.wd + b * 12544, 12544);
        }
        __syncwarp();
#pragma unroll
        for (int it = 0; it < 3; it++) {
            const int qd = warp + 12 * it;
            if (qd < 32) {
                const int row = qd * 4 + sub;
                float s0 = 0.f, s1 = 0.f, q0 = 0.f, q1 = 0.f;
#pragma unroll
                for (int i = 0; i < 7; i++) {
                    const uint32_t w[4] = {v[it][i].x, v[it][i].y, v[it][i].z, v[it][i].w};
#pragma unroll
                    for (int c = 0; c < 4; c++) {
                        const float d0 = bf_lo(w[c]), d1 = bf_hi(w[c]);
                        s0 += d0; s1 += d1;
                        q0 = fmaf(d0, d0, q0);
                        q1 = fmaf(d1, d1, q1);
                    }
                }
                float s = s0 + s1, q = q0 + q1;
#pragma unroll
                for (int o = 1; o < 8; o <<= 1) {
                    s += __shfl_xor_sync(0xffffffffu, s, o);
                    q += __shfl_xor_sync(0xffffffffu, q, o);
                }
                const float mean = s * (1.0f / D_);
                const float var = rbf(fmaxf(fmaf(-mean, mean, q * (1.0f / D_)), 0.f));
                const float den = rbf(sqrtf(rbf(var + 1e-5f)));
                const float rinv = 1.0f / den;
                const float rhi = rbf(rinv);
                const uint32_t m2 = pack_bf16(mean, mean), rhi2 = pack_bf16(rhi, rhi), rlo2 = pack_bf16(rinv - rhi, rinv - rhi);
                const uint32_t dst = sb + S1_XN + row * 128 + ((l8 ^ (row & 7)) << 4);
#pragma unroll
                for (int i = 0; i < 7; i++) {
                    const uint32_t w[4] = {v[it][i].x, v[it][i].y, v[it][i].z, v[it][i].w};
                    uint32_t o[4];
#pragma unroll
                    for (int c = 0; c < 4; c++) {
                        const uint32_t xc = hsub2(w[c], m2);
                        o[c] = hfma2(xc, rhi2, hmul2(xc, rlo2));
                    }
                    asm volatile("st.shared.v4.b32 [%0], {%1, %2, %3, %4};" ::"r"(dst + i * 16384), "r"(o[0]), "r"(o[1]), "r"(o[2]), "r"(o[3]) : "memory");
                }
            }
        }
        fence_async();
        __syncthreads();
    }

    if (warp >= 8) {
        asm volatile("setmaxnreg.dec.sync.aligned.u32 40;");
        if (warp == 8) {
            if (lane == 0) {
                int st = 0;
                uint32_t ph = 0;
                for (int p = 0; p < npass; p++) {
                    const int slab = pass_slab(j, p);
                    for (int kb = p ? 0 : S1_STAGES; kb < 7; kb++) {
                        mbar_wait(sb + BAR_E1 + 8 * st, ph);
                        const uint32_t dst = sb + S1_B + st * 16384 + rank * 8192;
                        const uint32_t fb = sb + BAR_F1 + 8 * st;
                        mbar_expect(fb, 16384);
                        if (slab >= 0) {
                            tma_load_mc(dst, rank ? &tm.wu : &tm.wg, fb, slab * 64, kb * 64);
                        } else {
                            const int a = 2 * j + rank;
                            tma_load_mc(dst, a < 7 ? &tm.hre : &tm.him, fb, kb * 64, (a < 7 ? a : a - 7) * 64);
                        }
                        if (++st == S1_STAGES) { st = 0; ph ^= 1; }
                        if (p == 1 && part < 2) {
                            for (int q = kb; q < 16; q += 7) tma_prefetch(part ? &tm.sim : &tm.sre, (2 * q + n) * 64, rb * 128);
                        }
                    }
                }
                if (part < 3) {
                    mbar_wait(sb + BAR_S1DONE, 0);
                    st = 0; ph = 1;
                    if (part < 2) {
                        const CUtensorMap* ma = part ? &tm.sim : &tm.sre;
                        for (int g = 0; g < 32; g++) {
                            mbar_wait(sb + BAR_E2 + 8 * st, ph);
                            const uint32_t dst = sb + st * Y_STAGE;
                            const uint32_t fb = sb + BAR_F2 + 8 * st;
                            mbar_expect(fb, Y_STAGE);
                            tma_load(dst, ma, fb, g * 64, rb * 128);
                            dep_wait(sb, (g >> 1) + 1);
                            tma_load_mc(dst + 16384 + rank * 14336, &tm.abT, fb, g * 64, part * 448 + n * 224 + rank * 112);
                            if (++st == Y_STAGES) { st = 0; ph ^= 1; }
                        }
                    } else {
                        for (int g = 0; g < 28; g++) {
                            mbar_wait(sb + BAR_E2 + 8 * st, ph);
                            const uint32_t dst = sb + st * F_STAGE;
                            const uint32_t fb = sb + BAR_F2 + 8 * st;
                            mbar_expect(fb, F_STAGE);
                            tma_load_mc(dst + 16384 + (2 * rank) * 8192, &tm.wd, fb, n * 224 + (2 * rank) * 64, g * 64);
                            tma_load_mc(dst + 16384 + (2 * rank + 1) * 8192, &tm.wd, fb, n * 224 + (2 * rank + 1) * 64, g * 64);
                            dep_wait(sb, g + 1);
                            tma_load(dst, &tm.h, fb, g * 64, rb * 128);
                            if (++st == F_STAGES) { st = 0; ph ^= 1; }
                        }
                    }
                }
            }
        } else if (warp == 9) {
            if (part < 3) {
                const int ndep = part < 2 ? 16 : 29;
                const unsigned int epoch = *(volatile unsigned int*)&g_fl.done / gridDim.x + 1;
                const unsigned int* f = part < 2 ? &g_fl.ab[lane & 15] : (lane < 28 ? &g_fl.h[rb * 28 + lane] : &g_fl.y[rb * 2 + n]);
                const unsigned int target = (part < 2 ? 7 : (lane < 27 ? 1 : 2)) * epoch;
                bool ok = lane >= ndep;
                int published = 0;
                for (int spins = 0; published < ndep && spins < (1 << 22); spins++) {
                    if (!ok) {
                        unsigned int v;
                        asm volatile("ld.acquire.gpu.global.u32 %0, [%1];" : "=r"(v) : "l"(f) : "memory");
                        ok = (int)(v - target) >= 0;
                    }
                    const unsigned int m = __ballot_sync(0xffffffffu, ok);
                    const int cnt = min(__ffs(~m) - 1, ndep);
                    if (m == 0xffffffffu || cnt > published) {
                        published = (m == 0xffffffffu) ? ndep : cnt;
                        fence_async_all();
                        __syncwarp();
                        if (lane == 0) asm volatile("st.release.cta.shared.u32 [%0], %1;" ::"r"(sb + DEP_CNT), "r"(published) : "memory");
                    }
                }
                if (published < ndep && lane == 0)
                    asm volatile("st.release.cta.shared.u32 [%0], %1;" ::"r"(sb + DEP_CNT), "r"(ndep) : "memory");
            }
        } else if (warp == 10) {
            if (lane == 0) {
                for (int p = 0; p < npass; p++) {
                    const int slab = pass_slab(j, p);
                    mbar_wait(sb + BAR_SF, p & 1);
                    if (slab == 27) tma_store(&tm.h64, sb + STG, slab * 64, rb * 128 + n * 64);
                    else if (slab >= 0) tma_store(&tm.h, sb + STG, slab * 64, rb * 128);
                    else {
                        tma_store(&tm.abT_st, sb + S1_B, rb * 128 + 64, j * 128);
                        bulk_commit();
                        tma_store(&tm.abT_st, sb + STG, rb * 128, j * 128);
                    }
                    bulk_commit();
                    if (slab < 0) {
                        asm volatile("cp.async.bulk.wait_group.read 1;" ::: "memory");
                        for (int w = 0; w < 4; w++) mbar_arrive_both(sb + BAR_E1);
                    }
                    bulk_wait_read0();
                    asm volatile("st.release.cta.shared.u32 [%0], %1;" ::"r"(sb + SE_CNT), "r"(p + 1) : "memory");
                    bulk_wait0();
                    fence_async_all();
                    flag_add(slab >= 0 ? &g_fl.h[rb * 28 + slab] : &g_fl.ab[rb]);
                }
            }
        }
        __syncwarp();
    } else {
        asm volatile("setmaxnreg.inc.sync.aligned.u32 232;");
        const int wg = warp >> 2, wl = warp & 3;
        const int qd = lane & 3;
        {
            float acc[2][64];
            for (int p = wg; p < npass; p += 2) {
                const int slab = pass_slab(j, p);
                if (p > 0) bar_sync(4 + (p & 1), 256);
                const int handoff = (p + 1 < npass) ? 4 + ((p + 1) & 1) : 0;
                if (slab == 27) s1_mainloop<2>(acc, sb, p, lane, handoff, n);
                else if (slab >= 0) s1_mainloop<1>(acc, sb, p, lane, handoff);
                else s1_mainloop<0>(acc, sb, p, lane, handoff);
                if (p + 2 >= npass && part < 3 && lane == 0) mbar_arrive_both(sb + BAR_S1DONE);

                const uint32_t srow = sb + STG + (wl * 16 + (lane & 7) + ((lane >> 3) & 1) * 8) * 128;
                if (slab >= 0) {
                    uint32_t hv[2][16];
#pragma unroll
                    for (int mh = 0; mh < 2; mh++) {
                        if (mh == 0 || slab != 27) {
#pragma unroll
                            for (int i = 0; i < 16; i++) {
                                const uint32_t g2 = pack_bf16(acc[mh][2 * i], acc[mh][2 * i + 1]);
                                const uint32_t u2 = pack_bf16(acc[mh][32 + 2 * i], acc[mh][32 + 2 * i + 1]);
                                const uint32_t a2 = pack_bf16(gelu_tanh(bf_lo(g2)), gelu_tanh(bf_hi(g2)));
                                hv[mh][i] = hmul2(a2, u2);
                            }
                        }
                    }
                    cnt_wait(sb + SE_CNT, p);
#pragma unroll
                    for (int mh = 0; mh < 2; mh++) {
                        if (mh == 0 || slab != 27) {
#pragma unroll
                            for (int jj = 0; jj < 8; jj += 2)
                                stmat4(srow + mh * 8192 + (((jj + (lane >> 4)) ^ (lane & 7)) << 4),
                                       hv[mh][2 * jj], hv[mh][2 * jj + 1], hv[mh][2 * jj + 2], hv[mh][2 * jj + 3]);
                        }
                    }
                } else {
                    bar_sync(2, 128);
#pragma unroll
                    for (int hf = 0; hf < 2; hf++) {
#pragma unroll
                        for (int mh = 0; mh < 2; mh++) {
#pragma unroll
                            for (int jj = 0; jj < 8; jj += 2) {
                                const int o = hf * 32 + jj * 4;
                                stmat4(srow - hf * (STG - S1_B) + mh * 8192 + (((jj + (lane >> 4)) ^ (lane & 7)) << 4),
                                       pack_bf16(acc[mh][o], acc[mh][o + 1]), pack_bf16(acc[mh][o + 2], acc[mh][o + 3]),
                                       pack_bf16(acc[mh][o + 4], acc[mh][o + 5]), pack_bf16(acc[mh][o + 6], acc[mh][o + 7]));
                            }
                        }
                    }
                }
                fence_async();
                __syncwarp();
                if (lane == 0) mbar_arrive(sb + BAR_SF);
            }
        }
        if (part < 3) {
            {
                float acc[112];
                const size_t base = (size_t)(rb * 128 + wg * 64 + wl * 16 + (lane >> 2)) * D_ + n * 224 + qd * 8;
                if (part < 2) {
                    s2_mainloop<0>(acc, sb, wg, lane);
                    bar_sync(1, 256);
#pragma unroll
                    for (int i = 0; i < 14; i++)
                        asm volatile("st.shared.v4.b32 [%0], {%1, %2, %3, %4};" ::"r"(sb + (i * 256 + tid) * 16),
                                     "r"(pack_bf16(acc[8 * i], acc[8 * i + 1])), "r"(pack_bf16(acc[8 * i + 2], acc[8 * i + 3])),
                                     "r"(pack_bf16(acc[8 * i + 4], acc[8 * i + 5])), "r"(pack_bf16(acc[8 * i + 6], acc[8 * i + 7])) : "memory");
                    fence_async();
                    bar_sync(1, 256);
                    if (tid == 0) {
                        uint4* dst = g_y + (size_t)((part * 32 + rb * 2 + n) * 14) * 256;
                        asm volatile("cp.async.bulk.global.shared::cta.bulk_group [%0], [%1], %2;" ::"l"(dst), "r"(sb), "r"(14 * 256 * 16) : "memory");
                        bulk_commit();
                        bulk_wait0();
                        fence_async_all();
                        flag_add(&g_fl.y[rb * 2 + n]);
                    }
                } else {
                    uint4 xv[14];
#pragma unroll
                    for (int i = 0; i < 14; i++)
                        xv[i] = __ldg(reinterpret_cast<const uint4*>(pt.x + base + (i / 7) * 8 * D_ + (i % 7) * 32));
                    s2_mainloop<1>(acc, sb, wg, lane);
                    uint32_t sg[56];
#pragma unroll
                    for (int i = 0; i < 56; i++) {
                        const uint32_t f2 = pack_bf16(acc[2 * i], acc[2 * i + 1]);
                        sg[i] = pack_bf16(silu(bf_lo(f2)), silu(bf_hi(f2)));
                    }
                    dep_wait(sb, 29);
                    const uint4* ysrc = g_y + (size_t)((rb * 2 + n) * 14) * 256 + tid;
                    uint4 yr[14], yi[14];
#pragma unroll
                    for (int i = 0; i < 14; i++) {
                        yr[i] = __ldcg(ysrc + i * 256);
                        yi[i] = __ldcg(ysrc + (32 * 14 + i) * 256);
                    }
#pragma unroll
                    for (int i = 0; i < 14; i++) {
                        sg[4 * i + 0] = hmul2(hsub2(yr[i].x, yi[i].x), sg[4 * i + 0]);
                        sg[4 * i + 1] = hmul2(hsub2(yr[i].y, yi[i].y), sg[4 * i + 1]);
                        sg[4 * i + 2] = hmul2(hsub2(yr[i].z, yi[i].z), sg[4 * i + 2]);
                        sg[4 * i + 3] = hmul2(hsub2(yr[i].w, yi[i].w), sg[4 * i + 3]);
                    }
#pragma unroll
                    for (int hh = 0; hh < 2; hh++) {
#pragma unroll
                        for (int g4 = 0; g4 < 7; g4++) {
                            uint32_t r[4];
#pragma unroll
                            for (int t = 0; t < 4; t++) r[t] = sg[(g4 * 4 + t) * 2 + hh];
                            quad_transpose(r, qd);
                            const uint4 xx = xv[hh * 7 + g4];
                            *reinterpret_cast<uint4*>(pt.out + base + hh * 8 * D_ + g4 * 32) =
                                make_uint4(hadd2(xx.x, r[0]), hadd2(xx.y, r[1]), hadd2(xx.z, r[2]), hadd2(xx.w, r[3]));
                        }
                    }
                }
            }
        }
    }
    __syncthreads();
    if (tid == 0) {
        atomicAdd(&g_fl.done, 1u);
    }
}

typedef CUresult (*EncFn)(CUtensorMap*, CUtensorMapDataType, cuuint32_t, void*, const cuuint64_t*, const cuuint64_t*,
                          const cuuint32_t*, const cuuint32_t*, CUtensorMapInterleave, CUtensorMapSwizzle,
                          CUtensorMapL2promotion, CUtensorMapFloatOOBfill);

void make_map(EncFn enc, CUtensorMap* m, const void* ptr, int rows, int cols, int box_rows, int box_cols, int pitch = 0) {
    const bool swz = true;
    cuuint64_t gd[2] = {(cuuint64_t)cols, (cuuint64_t)rows};
    cuuint64_t gs[1] = {(cuuint64_t)(pitch ? pitch : cols) * 2};
    cuuint32_t bx[2] = {(cuuint32_t)box_cols, (cuuint32_t)box_rows};
    cuuint32_t es[2] = {1, 1};
    enc(m, CU_TENSOR_MAP_DATA_TYPE_BFLOAT16, 2, const_cast<void*>(ptr), gd, gs, bx, es, CU_TENSOR_MAP_INTERLEAVE_NONE,
        swz ? CU_TENSOR_MAP_SWIZZLE_128B : CU_TENSOR_MAP_SWIZZLE_NONE, CU_TENSOR_MAP_L2_PROMOTION_L2_128B,
        CU_TENSOR_MAP_FLOAT_OOB_FILL_NONE);
}

}

extern "C" void kernel_launch(void* const* d_in, const int* in_sizes, int n_in, void* d_out, int out_size) {
    Ptrs pt;
    pt.x = (const __nv_bfloat16*)d_in[0];
    pt.hre = (const __nv_bfloat16*)d_in[3];
    pt.him = (const __nv_bfloat16*)d_in[4];
    pt.wg = (const __nv_bfloat16*)d_in[6];
    pt.wu = (const __nv_bfloat16*)d_in[7];
    pt.wd = (const __nv_bfloat16*)d_in[8];
    pt.out = (__nv_bfloat16*)d_out;

    void* fn = nullptr;
    cudaDriverEntryPointQueryResult qr;
    cudaGetDriverEntryPoint("cuTensorMapEncodeTiled", &fn, cudaEnableDefault, &qr);
    EncFn enc = (EncFn)fn;
    void *p_abT, *p_h;
    cudaGetSymbolAddress(&p_abT, g_abT);
    cudaGetSymbolAddress(&p_h, g_h);

    Maps tm;
    make_map(enc, &tm.wg, d_in[6], D_, F_, 64, 64);
    make_map(enc, &tm.wu, d_in[7], D_, F_, 64, 64);
    make_map(enc, &tm.hre, d_in[3], D_, D_, 64, 64);
    make_map(enc, &tm.him, d_in[4], D_, D_, 64, 64);
    make_map(enc, &tm.h, p_h, S_, F_, 128, 64);
    make_map(enc, &tm.h64, p_h, S_, F_, 64, 64);
    make_map(enc, &tm.abT, p_abT, 896, S_, 112, 64, ABP);
    make_map(enc, &tm.abT_st, p_abT, 896, S_, 128, 64, ABP);
    make_map(enc, &tm.sre, d_in[1], S_, S_, 128, 64);
    make_map(enc, &tm.sim, d_in[2], S_, S_, 128, 64);
    make_map(enc, &tm.wd, d_in[8], F_, D_, 64, 64);

    cudaFuncSetAttribute(fused_kernel, cudaFuncAttributeMaxDynamicSharedMemorySize, SMEM_BYTES);

    cudaLaunchAttribute at[1];
    at[0].id = cudaLaunchAttributeClusterDimension;
    at[0].val.clusterDim.x = 2; at[0].val.clusterDim.y = 1; at[0].val.clusterDim.z = 1;
    cudaLaunchConfig_t cfg = {};
    cfg.gridDim = dim3(128); cfg.blockDim = dim3(384); cfg.stream = cudaStreamPerThread;
    cfg.attrs = at; cfg.numAttrs = 1;
    cfg.dynamicSmemBytes = SMEM_BYTES;
    cudaLaunchKernelEx(&cfg, fused_kernel, pt, tm);
}
```
